```python
import torch

def _softmax(x, axis=-1):
    return torch.softmax(x, dim=axis)
def _gelu(x):
    return torch.nn.functional.gelu(x, approximate="tanh")
def _silu(x):
    return torch.nn.functional.silu(x)
def _sigmoid(x):
    return torch.sigmoid(x)
def _layernorm(x, axis=-1, eps=1e-5):
    m = x.mean(dim=axis, keepdim=True)
    v = x.var(dim=axis, keepdim=True, unbiased=False)
    return (x - m) / torch.sqrt(v + eps)
def _scatter_add(tgt, idx, src, axis=0):
    return tgt.clone().index_add_(axis, idx, src)
def _segment_sum(src, seg, n):
    out = torch.zeros((n,) + src.shape[1:], dtype=src.dtype)
    return out.index_add_(0, seg, src)
def _pad(x, pw):
    flat = tuple(v for pair in reversed(pw) for v in pair)
    return torch.nn.functional.pad(x, flat)

kernel_name = 'parallel_sum__compressed_kv_cla__glu_gated_glu__decode'

def setup_inputs():

    _w = (lambda a: (lambda t: t.to(torch.bfloat16) if t.is_floating_point() else t)(torch.as_tensor(a)))
    def _A_setup():
        B, H, Sq, Sk, D, M = 2, 32, 1, 4096, 128, 512
        Dc = 4 * D
        return {
            "x": _w((lambda *s: torch.randn(*s, dtype=torch.bfloat16) * 0.05)(B, Sq, M)),
            "c_kv": _w((lambda *s: torch.randn(*s, dtype=torch.bfloat16) * 1.6)(B, Sk, Dc)),
            "w_q": _w((lambda *s: torch.randn(*s, dtype=torch.bfloat16) * 1.6)(M, H, D) * (M ** -0.5)),
            "w_uk": _w((lambda *s: torch.randn(*s, dtype=torch.bfloat16) * 1.6)(Dc, H, D) * (Dc ** -0.5)),
            "w_uv": _w((lambda *s: torch.randn(*s, dtype=torch.bfloat16) * 1.6)(Dc, H, D) * (Dc ** -0.5)),
            "w_o": _w((lambda *s: torch.randn(*s, dtype=torch.bfloat16) * 1.6)(H, D, M) * ((H * D) ** -0.5)),
        }
    _A_in = _A_setup()

    def _B_setup():
        B, S, D, F = 2, 1, 512, 1376
        return {
            "x": _w((lambda *s: torch.randn(*s, dtype=torch.bfloat16) * 0.05)(B, S, D)),
            "w_gate": _w((lambda *s: torch.randn(*s, dtype=torch.bfloat16) * 0.1)(D, F)),
            "w_up": _w((lambda *s: torch.randn(*s, dtype=torch.bfloat16) * 0.05)(D, F)),
            "w_down": _w((lambda *s: torch.randn(*s, dtype=torch.bfloat16) * 0.05)(F, D)),
        }
    _B_in = _B_setup()

    return {
        "A_x": _A_in["x"],
        "A_c_kv": _A_in["c_kv"],
        "A_w_q": _A_in["w_q"],
        "A_w_uk": _A_in["w_uk"],
        "A_w_uv": _A_in["w_uv"],
        "A_w_o": _A_in["w_o"],
        "B_x": _B_in["x"],
        "B_w_gate": _B_in["w_gate"],
        "B_w_up": _B_in["w_up"],
        "B_w_down": _B_in["w_down"],
    }

def reference(A_x, A_c_kv, A_w_q, A_w_uk, A_w_uv, A_w_o, B_x, B_w_gate, B_w_up, B_w_down):
    def _A_ref(x, c_kv, w_q, w_uk, w_uv, w_o):
        B, Sq, M = x.shape[0], x.shape[1], x.shape[2]
        Sk = c_kv.shape[1]
        H, D = w_q.shape[1], w_q.shape[2]
        q = torch.einsum("bqm,mhd->bhqd", x, w_q)
        k = torch.einsum("bkc,chd->bhkd", c_kv, w_uk)
        v = torch.einsum("bkc,chd->bhkd", c_kv, w_uv)
        scores = torch.einsum("bhqd,bhkd->bhqk", q, k) * (D ** -0.5)
        off = Sk - Sq
        qi = torch.arange(Sq)[:, None]
        kj = torch.arange(Sk)[None, :]
        cmask = kj <= (qi + off)
        scores = torch.where(cmask[None, None], scores, -1e9)
        p = _softmax(scores, axis=-1)
        ctx = torch.einsum("bhqk,bhkd->bhqd", p, v)
        return torch.einsum("bhqd,hdm->bqm", ctx, w_o)

    def _B_ref(x, w_gate, w_up, w_down):
        g = torch.einsum("bsd,df->bsf", x, w_gate)
        u = torch.einsum("bsd,df->bsf", x, w_up)
        h = _sigmoid(g) * u
        return torch.einsum("bsf,fd->bsd", h, w_down)

    x = A_x
    xn = _layernorm(x, axis=-1)
    return x + _A_ref(xn, A_c_kv, A_w_q, A_w_uk, A_w_uv, A_w_o) + _B_ref(xn, B_w_gate, B_w_up, B_w_down)
```

```cpp
#include <cuda_runtime.h>
#include <cuda_bf16.h>
#include <cuda.h>
#include <stdint.h>

namespace {

constexpr int NCTA     = 128;
constexpr int NTHREADS = 352;
constexpr int SPIN_LIMIT = 1 << 22;

constexpr uint32_t OFF_RA  = 0;
constexpr uint32_t OFF_RB  = 65536;
constexpr uint32_t OFF_R0  = 131072;
constexpr uint32_t OFF_R1  = 163840;
constexpr uint32_t OFF_QA  = 196608;
constexpr uint32_t OFF_OP  = 212992;
constexpr uint32_t OP_XN = 0, OP_Q = 32, OP_CL = 64, OP_CX = 96;
constexpr uint32_t OFF_HA  = OFF_OP + 2048 + 256;
constexpr uint32_t OFF_P0  = OFF_HA + 768;
constexpr uint32_t OFF_P1  = OFF_P0 + 2048;
constexpr uint32_t OFF_ST  = OFF_P1 + 2048;
constexpr uint32_t ST_WMAX = 0;
constexpr uint32_t ST_LSUM = 512;
constexpr uint32_t ST_M0   = 1024;
constexpr uint32_t ST_M1   = 1088;
constexpr uint32_t ST_LN   = 1152;
constexpr uint32_t ST_STG  = 1280;
constexpr uint32_t OFF_BAR = OFF_ST + 1792;
constexpr uint32_t OFF_STAMP = OFF_BAR + 256;
constexpr uint32_t SMEM_USED = OFF_STAMP + 256;
constexpr uint32_t SMEM_BYTES = SMEM_USED + 1024;
static_assert(SMEM_BYTES <= 232448, "smem");
static_assert((OFF_P0 % 128) == 0 && (OFF_HA % 128) == 0 && (OFF_ST % 16) == 0 && (OFF_BAR % 8) == 0, "align");

enum { B_WQ = 0, B_WUK = 1, B_CKV = 2  , B_WUV = 18, B_G1 = 19, B_WO = 20, B_WD = 21,
       B_EVXA = 22, B_EVX1 = 23, B_EVX2 = 24, B_EVX3 = 25,
       B_FREE0 = 26, B_FREE1 = 27, B_FREEA = 28, NBARS = 29 };
static_assert(NBARS * 8 <= 256, "bars");

struct Tune {
    float inv_rate;
    int   burst;
    int   piece;
    int   t_wuk, t_ckv0, t_ckv1, t_wuv, t_g1, t_wo, t_wd;
    int   d_ckv;
    int   bo_a, bo_1, bo_2, bo_3, bo_4;
    int   dl_2;
    int   mode;
};

struct Scratch {
    uint4 X2[128 * 64 * 16];
    uint4 XA[32 * 4 * 64];
    uint4 XG[32 * 4 * 64];
    uint4 X3[32 * 4 * 64];
    uint4 X4[4 * 32 * 64];
    uint4 X1[2 * 32 * 64];
    uint4 XS[32 * 64 * 2];
    unsigned epoch[NCTA * 8];
};

struct Params {
    const __nv_bfloat16* x;
    Scratch* sc;
    const char* p_wq;
    const char* p_wuk;
    __nv_bfloat16* out;
    const char *p_wuv, *p_wo, *p_wg, *p_wu, *p_wd;
    Tune tune;
    alignas(64) CUtensorMap wq, wuk, wuv, wo, ckv, wg, wu, wd;
};

__device__ Scratch g_scratch;
#define STAMP(i) do {} while (0)

__device__ __forceinline__ uint32_t smem_u32(const void* p) { return (uint32_t)__cvta_generic_to_shared(p); }
__device__ __forceinline__ unsigned long long gtime() {
    unsigned long long t; asm volatile("mov.u64 %0, %%globaltimer;" : "=l"(t)); return t;
}
__device__ __forceinline__ void mbar_init(uint32_t bar, uint32_t cnt) {
    asm volatile("mbarrier.init.shared::cta.b64 [%0], %1;" :: "r"(bar), "r"(cnt) : "memory");
}
__device__ __forceinline__ void mbar_expect_tx(uint32_t bar, uint32_t bytes) {
    asm volatile("mbarrier.arrive.expect_tx.shared::cta.b64 _, [%0], %1;" :: "r"(bar), "r"(bytes) : "memory");
}
__device__ __forceinline__ void mbar_arrive(uint32_t bar) {
    asm volatile("mbarrier.arrive.shared::cta.b64 _, [%0];" :: "r"(bar) : "memory");
}
__device__ __forceinline__ void mbar_wait(uint32_t bar, uint32_t parity) {
    uint32_t done; int it = 0;
    do {
        asm volatile("{\n.reg .pred p;\nmbarrier.try_wait.parity.shared::cta.b64 p, [%1], %2;\nselp.u32 %0, 1, 0, p;\n}"
                     : "=r"(done) : "r"(bar), "r"(parity) : "memory");
    } while (!done && ++it < SPIN_LIMIT);
    if (!done) __trap();
}
__device__ __forceinline__ void tma2d(uint32_t dst, const CUtensorMap* m, int c0, int c1, uint32_t bar) {
    asm volatile("cp.async.bulk.tensor.2d.shared::cluster.global.mbarrier::complete_tx::bytes [%0], [%1, {%3,%4}], [%2];"
                 :: "r"(dst), "l"(m), "r"(bar), "r"(c0), "r"(c1) : "memory");
}
__device__ __forceinline__ void tma3d(uint32_t dst, const CUtensorMap* m, int c0, int c1, int c2, uint32_t bar) {
    asm volatile("cp.async.bulk.tensor.3d.shared::cluster.global.mbarrier::complete_tx::bytes [%0], [%1, {%3,%4,%5}], [%2];"
                 :: "r"(dst), "l"(m), "r"(bar), "r"(c0), "r"(c1), "r"(c2) : "memory");
}
__device__ __forceinline__ void tma2d_pf(const CUtensorMap* m, int c0, int c1) {
    asm volatile("cp.async.bulk.prefetch.tensor.2d.L2.global.tile [%0, {%1,%2}];" :: "l"(m), "r"(c0), "r"(c1) : "memory");
}
__device__ __forceinline__ void bulk_pf(const void* src, uint32_t bytes) {
    asm volatile("cp.async.bulk.prefetch.L2.global [%0], %1;" :: "l"(src), "r"(bytes) : "memory");
}
__device__ __forceinline__ void pf_map(const CUtensorMap* m) {
    asm volatile("prefetch.tensormap [%0];" :: "l"(m) : "memory");
}
__device__ __forceinline__ void bar_sync(int id, int n) { asm volatile("bar.sync %0, %1;" :: "r"(id), "r"(n) : "memory"); }
__device__ __forceinline__ void bar_arrive(int id, int n) { asm volatile("bar.arrive %0, %1;" :: "r"(id), "r"(n) : "memory"); }
__device__ __forceinline__ void fence_async() { asm volatile("fence.proxy.async.shared::cta;" ::: "memory"); }

__device__ __forceinline__ void st_ll(uint4* p, uint32_t a, uint32_t b, uint32_t c, uint32_t d) {
    asm volatile("{\n.reg .b128 t;\nmov.b128 t, {%1,%2,%3,%4};\nst.relaxed.gpu.global.b128 [%0], t;\n}"
                 :: "l"(p), "r"(a), "r"(b), "r"(c), "r"(d) : "memory");
}
__device__ __forceinline__ uint4 ld_ll(const uint4* p) {
    uint4 v;
    asm volatile("{\n.reg .b128 t;\nld.relaxed.gpu.global.b128 t, [%4];\nmov.b128 {%0,%1,%2,%3}, t;\n}"
                 : "=r"(v.x), "=r"(v.y), "=r"(v.z), "=r"(v.w) : "l"(p) : "memory");
    return v;
}
__device__ __forceinline__ void spin_clk(int n) {
    uint32_t c0, c; asm volatile("mov.u32 %0, %%clock;" : "=r"(c0));
    do { asm volatile("mov.u32 %0, %%clock;" : "=r"(c)); } while ((int)(c - c0) < n);
}
__device__ __forceinline__ uint4 poll_ll(const uint4* p, uint32_t tag, int backoff) {
    uint4 v = ld_ll(p); int it = 0;
    while (((v.x ^ tag) & 1u) && ++it < SPIN_LIMIT) { spin_clk(backoff); v = ld_ll(p); }
    if ((v.x ^ tag) & 1u) __trap();
    v.x &= ~1u;
    return v;
}
template <int N>
__device__ __forceinline__ void poll_ll_n(uint4 (&v)[N], const uint4* p, int stride, uint32_t tag, int backoff) {
    uint32_t pend = 0; int it = 0;
#pragma unroll
    for (int i = 0; i < N; i++) v[i] = ld_ll(p + i * stride);
#pragma unroll
    for (int i = 0; i < N; i++) if ((v[i].x ^ tag) & 1u) pend |= 1u << i;
    while (pend && ++it < SPIN_LIMIT) {
        spin_clk(backoff);
#pragma unroll
        for (int i = 0; i < N; i++) if (pend & (1u << i)) v[i] = ld_ll(p + i * stride);
#pragma unroll
        for (int i = 0; i < N; i++) if (!((v[i].x ^ tag) & 1u)) pend &= ~(1u << i);
    }
    if (pend) __trap();
#pragma unroll
    for (int i = 0; i < N; i++) v[i].x &= ~1u;
}

__device__ __forceinline__ uint64_t mk_desc(uint32_t sa16, uint32_t lbo, uint32_t sbo, uint32_t swz) {
    const uint32_t lo = sa16 + ((lbo >> 4) << 16);
    const uint32_t hi = (sbo >> 4) | (swz << 30);
    return ((uint64_t)hi << 32) | lo;
}
__device__ __forceinline__ void wg_fence()  { asm volatile("wgmma.fence.sync.aligned;" ::: "memory"); }
__device__ __forceinline__ void wg_commit() { asm volatile("wgmma.commit_group.sync.aligned;" ::: "memory"); }
template <int N> __device__ __forceinline__ void wg_wait() { asm volatile("wgmma.wait_group.sync.aligned %0;" :: "n"(N) : "memory"); }

template <int TA, int TB>
__device__ __forceinline__ void mma_n8(float (&d)[4], uint64_t da, uint64_t db, int acc) {
    asm volatile("{\n.reg .pred p;\nsetp.ne.b32 p, %6, 0;\n"
                 "wgmma.mma_async.sync.aligned.m64n8k16.f32.bf16.bf16 {%0,%1,%2,%3}, %4, %5, p, 1, 1, %7, %8;\n}\n"
                 : "+f"(d[0]), "+f"(d[1]), "+f"(d[2]), "+f"(d[3])
                 : "l"(da), "l"(db), "r"(acc), "n"(TA), "n"(TB));
}
template <int TA, int TB>
__device__ __forceinline__ void mma_n16(float (&d)[8], uint64_t da, uint64_t db, int acc) {
    asm volatile("{\n.reg .pred p;\nsetp.ne.b32 p, %10, 0;\n"
                 "wgmma.mma_async.sync.aligned.m64n16k16.f32.bf16.bf16 {%0,%1,%2,%3,%4,%5,%6,%7}, %8, %9, p, 1, 1, %11, %12;\n}\n"
                 : "+f"(d[0]), "+f"(d[1]), "+f"(d[2]), "+f"(d[3]), "+f"(d[4]), "+f"(d[5]), "+f"(d[6]), "+f"(d[7])
                 : "l"(da), "l"(db), "r"(acc), "n"(TA), "n"(TB));
}

__device__ __forceinline__ float bf_round(float v) { return __bfloat162float(__float2bfloat16_rn(v)); }
__device__ __forceinline__ uint32_t pack_bf(float lo, float hi) {
    uint32_t r; asm("cvt.rn.bf16x2.f32 %0, %1, %2;" : "=r"(r) : "f"(hi), "f"(lo)); return r;
}
__device__ __forceinline__ float bf_lo(uint32_t w) { return __uint_as_float(w << 16); }
__device__ __forceinline__ float bf_hi(uint32_t w) { return __uint_as_float(w & 0xFFFF0000u); }
__device__ __forceinline__ float ex2(float v) { float r; asm("ex2.approx.ftz.f32 %0, %1;" : "=f"(r) : "f"(v)); return r; }
__device__ __forceinline__ void sts16(uint32_t a, float v) {
    unsigned short s = __bfloat16_as_ushort(__float2bfloat16_rn(v));
    asm volatile("st.shared.u16 [%0], %1;" :: "r"(a), "h"(s) : "memory");
}
__device__ __forceinline__ void sts32(uint32_t a, uint32_t v) { asm volatile("st.shared.u32 [%0], %1;" :: "r"(a), "r"(v) : "memory"); }
__device__ __forceinline__ void stsf(uint32_t a, float v) { asm volatile("st.shared.f32 [%0], %1;" :: "r"(a), "f"(v) : "memory"); }
__device__ __forceinline__ float ldsf(uint32_t a) { float v; asm volatile("ld.shared.f32 %0, [%1];" : "=f"(v) : "r"(a) : "memory"); return v; }
__device__ __forceinline__ float4 ldsf4(uint32_t a) {
    float4 v; asm volatile("ld.shared.v4.f32 {%0,%1,%2,%3}, [%4];" : "=f"(v.x), "=f"(v.y), "=f"(v.z), "=f"(v.w) : "r"(a) : "memory"); return v;
}
__device__ __forceinline__ void wait_until(unsigned long long t) { while (gtime() < t) {} }

__device__ __forceinline__ void gemv_mmajor(float (&acc)[4], uint32_t a_base, uint32_t b_base, int ksteps, int first_acc) {
#pragma unroll
    for (int ks = 0; ks < 8; ks++) {
        if (ks < ksteps)
            mma_n8<1, 0>(acc, mk_desc(a_base + ks * 128, 1024, 1024, 1), mk_desc(b_base + ks * 16, 128, 128, 0), (ks > 0) | first_acc);
    }
}

__device__ __forceinline__ float quad_reduce4(float v0, float v1, float v2, float v3, int lane) {
    const bool b1 = lane & 2, b0 = lane & 1;
    float k0 = b1 ? v2 : v0, k1 = b1 ? v3 : v1;
    float s0 = b1 ? v0 : v2, s1 = b1 ? v1 : v3;
    k0 += __shfl_xor_sync(0xffffffffu, s0, 2);
    k1 += __shfl_xor_sync(0xffffffffu, s1, 2);
    float k = b0 ? k1 : k0, s = b0 ? k0 : k1;
    k += __shfl_xor_sync(0xffffffffu, s, 1);
    return k;
}

__global__ void __cluster_dims__(2, 1, 1) __launch_bounds__(NTHREADS, 1)
mla_glu_kernel(const __grid_constant__ Params P)
{
    extern __shared__ uint8_t smem_raw[];
    const int tid = threadIdx.x, lane = tid & 31;
    const int bid = blockIdx.x;
    const unsigned long long t0 = gtime();
    if (tid == 256) {
        bulk_pf(P.x, 2048);
        asm volatile("prefetch.global.L2 [%0];" :: "l"(&P.sc->epoch[bid * 8]));
        if (P.tune.mode & 1) {
            const char* p = P.p_wq + (size_t)bid * 32768;
            bulk_pf(p, 16384); bulk_pf(p + 16384, 16384);
        }
    }
    const uint32_t sb = (smem_u32(smem_raw) + 1023u) & ~1023u;
    const uint32_t bars = sb + OFF_BAR;
    auto BAR = [&](int i) { return bars + 8u * i; };
    const int h = bid >> 2, j = bid & 3;
    if (tid == 288) {
        mbar_init(BAR(B_WQ), 1);
        asm volatile("fence.mbarrier_init.release.cluster;" ::: "memory");
        mbar_expect_tx(BAR(B_WQ), 32768);
        tma2d(sb + OFF_R0,         &P.wq, h * 128,      j * 128, BAR(B_WQ));
        tma2d(sb + OFF_R0 + 16384, &P.wq, h * 128 + 64, j * 128, BAR(B_WQ));
        STAMP(29);
#pragma unroll
        for (int i = 1; i < NBARS; i++) mbar_init(BAR(i), (i >= B_FREE0) ? 2 : 1);
        asm volatile("fence.mbarrier_init.release.cluster;" ::: "memory");
        fence_async();
    }
    const int warp = __shfl_sync(0xffffffffu, tid >> 5, 0);
    const int cid = bid >> 1, r = bid & 1;
    const uint32_t sd = (sb & 0x3FFFFu) >> 4;
    const int f0 = h < 22 ? 48 * h : 1056 + 32 * (h - 22);
    const int fvalid = h < 22 ? 48 : 32;
    Scratch* const sc = P.sc;

    if (warp >= 8) {
      if (warp == 9) {
        bar_arrive(0, NTHREADS);
        if (lane == 0) {
            pf_map(&P.wuk); pf_map(&P.ckv); pf_map(&P.wuv); pf_map(&P.wg); pf_map(&P.wu); pf_map(&P.wo); pf_map(&P.wd);
            const Tune& T = P.tune;
            if (T.t_wuk >= 0) wait_until(t0 + T.t_wuk); else mbar_wait(BAR(B_EVXA), 0);
            mbar_expect_tx(BAR(B_WUK), 32768);
            tma2d(sb + OFF_R1,         &P.wuk, h * 128,      j * 128, BAR(B_WUK));
            tma2d(sb + OFF_R1 + 16384, &P.wuk, h * 128 + 64, j * 128, BAR(B_WUK));
            if (T.t_ckv0 < 0) mbar_wait(BAR(B_EVX1), 0);
#pragma unroll 1
            for (int tu = 0; tu < 16; tu++) {
                const int t = tu >> 3, u = tu & 7;
                if (T.t_ckv0 >= 0) wait_until(t0 + (t ? T.t_ckv1 : T.t_ckv0) + u * T.d_ckv);
                mbar_expect_tx(BAR(B_CKV + tu), 8192);
                tma2d(sb + OFF_RA + tu * 8192, &P.ckv, u * 64, cid * 128 + t * 64, BAR(B_CKV + tu));
            }
            if (T.t_wuv >= 0) wait_until(t0 + T.t_wuv); else mbar_wait(BAR(B_CKV + 15 + T.t_wuv + 1), 0);
            mbar_wait(BAR(B_FREE1), 0);
            mbar_expect_tx(BAR(B_WUV), 32768);
            tma3d(sb + OFF_R1,         &P.wuv, h * 128,      j * 16, 0, BAR(B_WUV));
            tma3d(sb + OFF_R1 + 16384, &P.wuv, h * 128 + 64, j * 16, 0, BAR(B_WUV));
            if (T.t_g1 >= 0) wait_until(t0 + T.t_g1); else if (T.t_g1 == -1) mbar_wait(BAR(B_EVX2), 0);
            mbar_wait(BAR(B_FREE0), 0);
            mbar_expect_tx(BAR(B_G1), 32768);
            tma2d(sb + OFF_R0,         &P.wg, f0, j * 128, BAR(B_G1));
            tma2d(sb + OFF_R0 + 16384, &P.wu, f0, j * 128, BAR(B_G1));
            if (T.t_wo >= 0) wait_until(t0 + T.t_wo); else if (T.t_wo == -1) mbar_wait(BAR(B_EVX3), 0); else mbar_wait(BAR(B_EVX2), 0);
            mbar_wait(BAR(B_FREEA), 0);
            mbar_expect_tx(BAR(B_WO), 32768);
            tma2d(sb + OFF_RA,         &P.wo, j * 128,      h * 128, BAR(B_WO));
            tma2d(sb + OFF_RA + 16384, &P.wo, j * 128 + 64, h * 128, BAR(B_WO));
            if (T.t_wd >= 0) wait_until(t0 + T.t_wd);
            mbar_expect_tx(BAR(B_WD), 12288);
            tma2d(sb + OFF_RA + 32768,        &P.wd, j * 128,      f0, BAR(B_WD));
            tma2d(sb + OFF_RA + 32768 + 6144, &P.wd, j * 128 + 64, f0, BAR(B_WD));
        }
      } else if (warp == 8) {
        bar_arrive(0, NTHREADS);
        if (lane == 0) {
            STAMP(35);
            const Tune& T = P.tune;
            const float inv_rate = T.inv_rate;
            int cum = 32768 - T.burst;
            auto pace = [&](int bytes) {
                if (cum > 0) wait_until(t0 + (unsigned)((float)cum * inv_rate));
                cum += bytes;
            };
            auto lin = [&](const char* base, int per) {
                const char* p = base + (size_t)bid * per;
#pragma unroll 1
                for (int o = 0; o < per; o += T.piece) { int n = min(T.piece, per - o); pace(n); bulk_pf(p + o, n); }
            };
            lin(P.p_wuk, 32768);
#pragma unroll 1
            for (int tu = 0; tu < 8; tu++) { pace(8192); tma2d_pf(&P.ckv, ((tu & 3) * 2 + r) * 64, cid * 128 + (tu >> 2) * 64); }
            lin(P.p_wuv, 32768);
            lin(P.p_wg, 11008); lin(P.p_wu, 11008);
            lin(P.p_wo, 32768);
            lin(P.p_wd, 11008);
        }
      } else {
        const uint32_t ntag = sc->epoch[bid * 8] & 1u;
        if (ntag < 2 && lane == 0) STAMP(26);
#pragma unroll
        for (int i = 0; i < 2; i++) st_ll(sc->XA + (h * 4 + j) * 64 + i * 32 + lane, ntag, 0, 0, 0);
        st_ll(sc->X1 + ((lane >> 4) * 32 + h) * 64 + 16 * j + (lane & 15), ntag, 0, 0, 0);
        st_ll(sc->XS + ((16 * r + (lane >> 1)) * 64 + cid) * 2 + (lane & 1), ntag, 0, 0, 0);
#pragma unroll
        for (int i = 0; i < 2; i++) {
            st_ll(sc->X3 + (h * 4 + j) * 64 + i * 32 + lane, ntag, 0, 0, 0);
            st_ll(sc->XG + (h * 4 + j) * 64 + i * 32 + lane, ntag, 0, 0, 0);
            st_ll(sc->X4 + (j * 32 + h) * 64 + i * 32 + lane, ntag, 0, 0, 0);
        }
        uint4* px2 = sc->X2 + ((size_t)((16 * r) * 4 + (lane >> 4)) * 64 + cid) * 16 + (lane & 15);
#pragma unroll 4
        for (int i = 0; i < 32; i++)
            st_ll(px2 + i * (2 * 64 * 16), ntag, 0, 0, 0);
        if (lane == 0) STAMP(27);
        bar_sync(0, NTHREADS);
      }
      return;
    }

    const int g  = warp >> 2;
    const int w  = warp & 3;
    const int tg = tid & 127;
    const int rr = lane >> 2, q = lane & 3;
    const Tune& T = P.tune;

    if (tid == 0) STAMP(36);
    const unsigned ep = sc->epoch[bid * 8];
    const int fj = bid >> 5, fci = 2 * (bid & 31) + (warp & 1);
    const int fcol = 128 * fj + 64 * (fci >> 5) + 16 * ((fci & 31) >> 3) + (fci & 7) + 8 * (lane >> 4);
    const int fb = (lane >> 3) & 1;
    float xres = 0.f;
    if (w == 0) {
        const uint4* xp = reinterpret_cast<const uint4*>(P.x + g * 512 + lane * 16);
        const uint4 xa = xp[0], xb = xp[1];
        const float x0 = __bfloat162float(P.x[g * 512]);
        const uint32_t xw[8] = { xa.x, xa.y, xa.z, xa.w, xb.x, xb.y, xb.z, xb.w };
        float xv[16];
#pragma unroll
        for (int i = 0; i < 8; i++) { xv[2 * i] = bf_lo(xw[i]); xv[2 * i + 1] = bf_hi(xw[i]); }
        float s = 0.f, s2 = 0.f;
#pragma unroll
        for (int i = 0; i < 16; i++) { const float d = xv[i] - x0; s += d; s2 = fmaf(d, d, s2); }
        if (tid == 0 && s != 12345.f) STAMP(28);
#pragma unroll
        for (int o = 16; o; o >>= 1) { s += __shfl_xor_sync(0xffffffffu, s, o); s2 += __shfl_xor_sync(0xffffffffu, s2, o); }
        const float md = s * (1.0f / 512.0f);
        const float var = fmaxf(fmaf(-md, md, s2 * (1.0f / 512.0f)), 0.f);
        const float mb = bf_round(x0 + md);
        const float rs = __frcp_rn(bf_round(__fsqrt_rn(bf_round(bf_round(var) + 1e-5f))));
        if ((lane >> 3) == j) {
            uint32_t o[8];
#pragma unroll
            for (int i = 0; i < 8; i++) o[i] = pack_bf(bf_round(xv[2 * i] - mb) * rs, bf_round(xv[2 * i + 1] - mb) * rs);
            const uint32_t a = sb + OFF_OP + OP_XN + (lane & 7) * 256 + g * 16;
            asm volatile("st.shared.v4.u32 [%0], {%1,%2,%3,%4};" :: "r"(a), "r"(o[0]), "r"(o[1]), "r"(o[2]), "r"(o[3]) : "memory");
            asm volatile("st.shared.v4.u32 [%0], {%1,%2,%3,%4};" :: "r"(a + 128), "r"(o[4]), "r"(o[5]), "r"(o[6]), "r"(o[7]) : "memory");
        }
        if (tid == 0) STAMP(30);
        fence_async();
    } else if (warp == 1) {
        if (lane < 12) {
            const uint32_t a = sb + OFF_HA + (lane >> 1) * 128 + (lane & 1) * 16;
            asm volatile("st.shared.v4.u32 [%0], {%1,%1,%1,%1};" :: "r"(a), "r"(0) : "memory");
        }
        fence_async();
    }
    if (warp < 2) xres = __bfloat162float(P.x[fb * 512 + fcol]);
    const uint32_t tag = (ep + 1u) & 1u;

    const int qci = (h * 4 + j) * 64 + g * 32 + w * 8 + rr;
    bar_sync(0, NTHREADS);
    if (tid == 0) sc->epoch[bid * 8] = ep + 1u;
    if (tid == 0) { STAMP(0); }

    float acc[4];
    mbar_wait(BAR(B_WQ), 0);
    if (tid == 0) STAMP(1);
    wg_fence();
    gemv_mmajor(acc, sd + (OFF_R0 >> 4) + g * 1024, sd + ((OFF_OP + OP_XN) >> 4), 8, 0);
    wg_commit(); wg_wait<0>();
    if (tg == 0) mbar_arrive(BAR(B_FREE0));
    if (q == 0) st_ll(sc->XA + qci, (__float_as_uint(acc[0]) & ~1u) | tag, __float_as_uint(acc[1]), __float_as_uint(acc[2]), __float_as_uint(acc[3]));
    if (tid == 0) STAMP(6);
    {
        const int ci = tid >> 2, jj = tid & 3;
        uint4 v = poll_ll(sc->XA + (h * 4 + jj) * 64 + ci, tag, T.bo_a);
        if (tid == 0) STAMP(7);
        float s = quad_reduce4(__uint_as_float(v.x), __uint_as_float(v.y), __uint_as_float(v.z), __uint_as_float(v.w), lane);
        const int d = 64 * (ci >> 5) + 16 * ((ci & 31) >> 3) + (ci & 7) + 8 * (jj >> 1);
        sts16(sb + OFF_OP + OP_Q + (d >> 3) * 128 + (jj & 1) * 16 + (d & 7) * 2, s);
        fence_async();
    }
    bar_sync(3, 256);
    if (tid == 0) mbar_arrive(BAR(B_EVXA));
    if (tid == 0) STAMP(2);

    mbar_wait(BAR(B_WUK), 0);
    if (tid == 0) STAMP(3);
    wg_fence();
#pragma unroll
    for (int ks = 0; ks < 8; ks++)
        mma_n8<0, 0>(acc, mk_desc(sd + ((OFF_R1 + (ks >> 2) * 16384 + (ks & 3) * 32) >> 4) + g * 512, 16, 1024, 1),
                     mk_desc(sd + ((OFF_OP + OP_Q + ks * 256) >> 4), 128, 128, 0), ks > 0);
    wg_commit(); wg_wait<0>();
    if (tg == 0) mbar_arrive(BAR(B_FREE1));
    {
        const float qs = 0.08838834764831845f * 1.4426950408889634f;
        const uint32_t stg = sb + OFF_ST + ST_STG + warp * 64;
        if (q == 0) {
            sts16(stg + rr * 2,           acc[0] * qs);
            sts16(stg + 32 + rr * 2,      acc[1] * qs);
            sts16(stg + 16 + rr * 2,      acc[2] * qs);
            sts16(stg + 32 + 16 + rr * 2, acc[3] * qs);
        }
        __syncwarp();
        if (lane < 4) {
            uint4 v;
            asm volatile("ld.shared.v4.u32 {%0,%1,%2,%3}, [%4];" : "=r"(v.x), "=r"(v.y), "=r"(v.z), "=r"(v.w) : "r"(stg + lane * 16) : "memory");
            st_ll(sc->X1 + ((lane >> 1) * 32 + h) * 64 + 16 * j + 8 * g + 2 * w + (lane & 1), (v.x & ~1u) | tag, v.y, v.z, v.w);
        }
    }
    if (tid == 0) STAMP(4);
    {
        const uint4* src = sc->X1 + ((cid >> 5) * 32 + 16 * r) * 64;
        uint4 v[4];
        poll_ll_n<4>(v, src + tid, 256, tag, T.bo_1);
#pragma unroll
        for (int i = 0; i < 4; i++) {
            const int idx = i * 256 + tid, n = idx >> 6, kc = idx & 63;
            const uint32_t a = sb + OFF_QA + (kc >> 3) * 2048 + n * 128 + (((kc & 7) ^ (n & 7)) << 4);
            asm volatile("st.shared.v4.u32 [%0], {%1,%2,%3,%4};" :: "r"(a), "r"(v[i].x), "r"(v[i].y), "r"(v[i].z), "r"(v[i].w) : "memory");
        }
        fence_async();
    }
    bar_sync(3, 256);
    if (tid == 0) mbar_arrive(BAR(B_EVX1));
    if (tid == 0) STAMP(5);

    float o[4][8];
    const uint32_t st = sb + OFF_ST;
    auto scores = [&](int t) {
        float s[8];
        const uint32_t tile = sd + ((t ? OFF_RB : OFF_RA) >> 4);
#pragma unroll
        for (int u = 0; u < 8; u++) {
            mbar_wait(BAR(B_CKV + t * 8 + u), 0);
            wg_fence();
#pragma unroll
            for (int ks = 0; ks < 4; ks++)
                mma_n16<0, 0>(s, mk_desc(tile + ((u * 8192 + ks * 32) >> 4), 16, 1024, 1),
                              mk_desc(sd + ((OFF_QA + u * 2048 + ks * 32) >> 4), 16, 1024, 1), (u | ks) != 0);
            wg_commit();
        }
        wg_wait<0>();
        if (tg == 0) STAMP(8 + t * 4);
        float m[4];
#pragma unroll
        for (int i = 0; i < 4; i++) {
            m[i] = fmaxf(s[(i >> 1) * 4 + (i & 1)], s[(i >> 1) * 4 + (i & 1) + 2]);
#pragma unroll
            for (int x = 4; x < 32; x <<= 1) m[i] = fmaxf(m[i], __shfl_xor_sync(0xffffffffu, m[i], x));
        }
        const uint32_t wm = st + ST_WMAX + t * 256;
        if (rr == 0) {
#pragma unroll
            for (int i = 0; i < 4; i++) stsf(wm + (((i >> 1) * 8 + 2 * q + (i & 1)) * 4 + w) * 4, m[i]);
        }
        bar_sync(1 + t, 128);
        uint32_t pk[4]; float l[4];
#pragma unroll
        for (int i = 0; i < 4; i++) {
            const int col = (i >> 1) * 8 + 2 * q + (i & 1);
            float4 t4 = ldsf4(wm + col * 16);
            float mm = fmaxf(fmaxf(t4.x, t4.y), fmaxf(t4.z, t4.w));
            if (t) mm = fmaxf(mm, ldsf(st + ST_M0 + col * 4));
            m[i] = mm;
        }
        float p[8];
#pragma unroll
        for (int i = 0; i < 8; i++) p[i] = ex2(s[i] - m[(i >> 2) * 2 + (i & 1)]);
        pk[0] = pack_bf(p[0], p[1]); pk[1] = pack_bf(p[2], p[3]); pk[2] = pack_bf(p[4], p[5]); pk[3] = pack_bf(p[6], p[7]);
        const uint32_t pb = sb + (t ? OFF_P1 : OFF_P0) + w * 512 + lane * 4;
        sts32(pb, pk[0]); sts32(pb + 256, pk[1]); sts32(pb + 128, pk[2]); sts32(pb + 256 + 128, pk[3]);
        fence_async();
#pragma unroll
        for (int i = 0; i < 4; i++) {
            l[i] = p[(i >> 1) * 4 + (i & 1)] + p[(i >> 1) * 4 + (i & 1) + 2];
#pragma unroll
            for (int x = 4; x < 32; x <<= 1) l[i] += __shfl_xor_sync(0xffffffffu, l[i], x);
        }
        if (rr == 0) {
#pragma unroll
            for (int i = 0; i < 4; i++) {
                const int col = (i >> 1) * 8 + 2 * q + (i & 1);
                stsf(st + ST_LSUM + t * 256 + (col * 4 + w) * 4, l[i]);
                if (w == 0) stsf(st + (t ? ST_M1 : ST_M0) + col * 4, m[i]);
            }
        }
    };
    auto pv = [&](int t) {
        const uint32_t tile = sd + ((t ? OFF_RB : OFF_RA) >> 4) + g * 2048;
        const uint32_t pb = sd + ((t ? OFF_P1 : OFF_P0) >> 4);
        wg_fence();
#pragma unroll
        for (int mt = 0; mt < 4; mt++) {
#pragma unroll
            for (int ks = 0; ks < 4; ks++)
                mma_n16<1, 1>(o[mt], mk_desc(tile + ((mt * 8192 + ks * 2048) >> 4), 1024, 1024, 1),
                              mk_desc(pb + ks * 32, 256, 128, 0), t | (ks > 0));
        }
        wg_commit();
    };

    if (g == 0) scores(0);
    bar_sync(3, 256);
    if (tid == 0) STAMP(9);
    pv(0);
    if (g == 1) { wg_wait<0>(); if (tg == 0) mbar_arrive(BAR(B_FREEA)); scores(1); }
    else        { wg_wait<0>(); if (tg == 0) mbar_arrive(BAR(B_FREEA)); }
    bar_sync(3, 256);
    if (tid == 0) STAMP(13);
    {
        if (warp == 0) {
            const int col = lane >> 1;
            const float m0 = ldsf(st + ST_M0 + col * 4), m1 = ldsf(st + ST_M1 + col * 4);
            const float4 a = ldsf4(st + ST_LSUM + col * 16), b = ldsf4(st + ST_LSUM + 256 + col * 16);
            const float l = ((a.x + a.y) + (a.z + a.w)) * ex2(m0 - m1) + ((b.x + b.y) + (b.z + b.w));
            st_ll(sc->XS + ((16 * r + (lane >> 1)) * 64 + cid) * 2 + (lane & 1), tag, __float_as_uint(m1), __float_as_uint(l), 0);
        }
#pragma unroll
        for (int i = 0; i < 4; i++) {
            const int col = (i >> 1) * 8 + 2 * q + (i & 1);
            const float f = ex2(ldsf(st + ST_M0 + col * 4) - ldsf(st + ST_M1 + col * 4));
#pragma unroll
            for (int mt = 0; mt < 4; mt++) { o[mt][(i >> 1) * 4 + (i & 1)] *= f; o[mt][(i >> 1) * 4 + (i & 1) + 2] *= f; }
        }
    }
    pv(1);
    uint4* const pX2 = sc->X2 + ((size_t)((16 * r + 2 * q) * 4 + w) * 64 + cid) * 16 + g * 8 + rr;
    wg_wait<0>();
    if (tid == 0) STAMP(14);
#pragma unroll
    for (int ii = 0; ii < 4; ii++) {
        const int c0 = (ii >> 1) * 4 + (ii & 1);
        st_ll(pX2 + ((ii >> 1) * 8 + (ii & 1)) * (4 * 64 * 16),
              (pack_bf(o[0][c0], o[0][c0 + 2]) & ~1u) | tag, pack_bf(o[1][c0], o[1][c0 + 2]),
              pack_bf(o[2][c0], o[2][c0 + 2]), pack_bf(o[3][c0], o[3][c0 + 2]));
    }
    if (tid == 0) STAMP(15);

    {
        const int ci = tg & 15, pg = tg >> 4;
        const uint4* src = sc->X2 + ((size_t)bid * 64 + 32 * g + pg) * 16 + ci;
        spin_clk(T.dl_2);
        uint4 dv[4];
#pragma unroll
        for (int i = 0; i < 4; i++) dv[i] = ld_ll(src + i * 8 * 16);
        uint4 sv = poll_ll(sc->XS + (h * 64 + 32 * g + lane) * 2, tag, T.bo_2);
        const float mp = __uint_as_float(sv.y), lp = __uint_as_float(sv.z);
        float M = mp;
#pragma unroll
        for (int x = 16; x; x >>= 1) M = fmaxf(M, __shfl_xor_sync(0xffffffffu, M, x));
        const float wp = ex2(mp - M);
        float L = wp * lp;
#pragma unroll
        for (int x = 16; x; x >>= 1) L += __shfl_xor_sync(0xffffffffu, L, x);
        float a8[8];
#pragma unroll
        for (int i = 0; i < 8; i++) a8[i] = 0.f;
        {
            uint32_t pend = 0;
#pragma unroll
            for (int i = 0; i < 4; i++) if ((dv[i].x ^ tag) & 1u) pend |= 1u << i;
            int it = 0;
            while (pend && ++it < SPIN_LIMIT) {
                spin_clk(T.bo_2);
#pragma unroll
                for (int i = 0; i < 4; i++) if (pend & (1u << i)) dv[i] = ld_ll(src + i * 8 * 16);
#pragma unroll
                for (int i = 0; i < 4; i++) if (!((dv[i].x ^ tag) & 1u)) pend &= ~(1u << i);
            }
            if (pend) __trap();
        }
#pragma unroll
        for (int i = 0; i < 4; i++) {
            uint4 v = dv[i]; v.x &= ~1u;
            const float wi = __shfl_sync(0xffffffffu, wp, i * 8 + pg);
            a8[0] += wi * bf_lo(v.x); a8[1] += wi * bf_hi(v.x); a8[2] += wi * bf_lo(v.y); a8[3] += wi * bf_hi(v.y);
            a8[4] += wi * bf_lo(v.z); a8[5] += wi * bf_hi(v.z); a8[6] += wi * bf_lo(v.w); a8[7] += wi * bf_hi(v.w);
        }
#pragma unroll
        for (int i = 0; i < 8; i++) a8[i] += __shfl_xor_sync(0xffffffffu, a8[i], 16);
        const uint32_t red = sb + OFF_QA + g * 2048;
        if (lane < 16) {
            const uint32_t a = red + (w * 16 + ci) * 32;
            asm volatile("st.shared.v4.f32 [%0], {%1,%2,%3,%4};" :: "r"(a), "f"(a8[0]), "f"(a8[1]), "f"(a8[2]), "f"(a8[3]) : "memory");
            asm volatile("st.shared.v4.f32 [%0], {%1,%2,%3,%4};" :: "r"(a + 16), "f"(a8[4]), "f"(a8[5]), "f"(a8[6]), "f"(a8[7]) : "memory");
        }
        bar_sync(1 + g, 128);
        const int c2 = tg >> 3, e = tg & 7;
        const uint32_t a = red + c2 * 32 + e * 4;
        const float sum = (ldsf(a) + ldsf(a + 512)) + (ldsf(a + 1024) + ldsf(a + 1536));
        const int kg = ((c2 >> 3) * 4 + (e >> 1)) * 2 + (e & 1);
        sts16(sb + OFF_OP + OP_CL + kg * 128 + g * 16 + (c2 & 7) * 2, sum / L);
        fence_async();
    }
    bar_sync(3, 256);
    if (tid == 0) mbar_arrive(BAR(B_EVX2));
    if (tid == 0) STAMP(16);

    mbar_wait(BAR(B_WUV), 0);
    if (tid == 0) STAMP(17);
    wg_fence();
    gemv_mmajor(acc, sd + (OFF_R1 >> 4) + g * 1024, sd + ((OFF_OP + OP_CL) >> 4), 8, 0);
    wg_commit(); wg_wait<0>();
    if (q == 0) st_ll(sc->X3 + qci, (__float_as_uint(acc[0]) & ~1u) | tag, __float_as_uint(acc[1]), __float_as_uint(acc[2]), __float_as_uint(acc[3]));
    if (tid == 0) STAMP(18);

    mbar_wait(BAR(B_G1), 0);
    if (tid == 0) STAMP(19);
    wg_fence();
    gemv_mmajor(acc, sd + (OFF_R0 >> 4) + g * 1024, sd + ((OFF_OP + OP_XN) >> 4), 8, 0);
    wg_commit(); wg_wait<0>();
    if (q == 0) st_ll(sc->XG + qci, (__float_as_uint(acc[0]) & ~1u) | tag, __float_as_uint(acc[1]), __float_as_uint(acc[2]), __float_as_uint(acc[3]));
    {
        const int ci = tid >> 2, jj = tid & 3;
        const int pi = tid >> 3, gu = (tid >> 2) & 1;
        const uint4* p3 = sc->X3 + (h * 4 + jj) * 64 + ci;
        const uint4* pg = sc->XG + (h * 4 + jj) * 64 + gu * 32 + pi;
        uint4 v3, vg; bool n3 = true, ng = true; int it = 0;
        do {
            if (it) spin_clk(T.bo_3);
            if (n3) v3 = ld_ll(p3);
            if (ng) vg = ld_ll(pg);
            n3 = (v3.x ^ tag) & 1u; ng = (vg.x ^ tag) & 1u;
        } while ((n3 || ng) && ++it < SPIN_LIMIT);
        if (n3 || ng) __trap();
        float s = quad_reduce4(__uint_as_float(v3.x & ~1u), __uint_as_float(v3.y), __uint_as_float(v3.z), __uint_as_float(v3.w), lane);
        const int d = 64 * (ci >> 5) + 16 * ((ci & 31) >> 3) + (ci & 7) + 8 * (jj >> 1);
        sts16(sb + OFF_OP + OP_CX + (d >> 3) * 128 + (jj & 1) * 16 + (d & 7) * 2, s);
        s = quad_reduce4(__uint_as_float(vg.x & ~1u), __uint_as_float(vg.y), __uint_as_float(vg.z), __uint_as_float(vg.w), lane);
        s = bf_round(s);
        const float other = __shfl_xor_sync(0xffffffffu, s, 4);
        const int f = 16 * (pi >> 3) + (pi & 7) + 8 * (jj >> 1);
        if (gu == 0 && f < fvalid) {
            const float sg = bf_round(__fdividef(1.0f, 1.0f + __expf(-s)));
            sts16(sb + OFF_HA + (f >> 3) * 128 + (jj & 1) * 16 + (f & 7) * 2, sg * other);
        }
        fence_async();
    }
    bar_sync(3, 256);
    if (tid == 0) mbar_arrive(BAR(B_EVX3));
    if (tid == 0) STAMP(21);

    mbar_wait(BAR(B_WO), 0);
    if (tid == 0) STAMP(22);
    wg_fence();
    gemv_mmajor(acc, sd + (OFF_RA >> 4) + g * 1024, sd + ((OFF_OP + OP_CX) >> 4), 8, 0);
    wg_commit();
    mbar_wait(BAR(B_WD), 0);
    if (tid == 0) STAMP(23);
    wg_fence();
    gemv_mmajor(acc, sd + ((OFF_RA + 32768) >> 4) + g * 384, sd + (OFF_HA >> 4), 3, 1);
    wg_commit(); wg_wait<0>();
    if (q == 0) st_ll(sc->X4 + (j * 32 + h) * 64 + g * 32 + w * 8 + rr, (__float_as_uint(acc[0]) & ~1u) | tag, __float_as_uint(acc[1]), __float_as_uint(acc[2]), __float_as_uint(acc[3]));
    if (tid == 0) STAMP(24);

    if (warp < 2) {
        uint4 v = poll_ll(sc->X4 + (fj * 32 + lane) * 64 + fci, tag, T.bo_4);
        float v0 = __uint_as_float(v.x), v1 = __uint_as_float(v.y), v2 = __uint_as_float(v.z), v3 = __uint_as_float(v.w);
        const bool b4 = lane & 16, b3 = lane & 8;
        float k0 = b4 ? v2 : v0, k1 = b4 ? v3 : v1, s0 = b4 ? v0 : v2, s1 = b4 ? v1 : v3;
        k0 += __shfl_xor_sync(0xffffffffu, s0, 16);
        k1 += __shfl_xor_sync(0xffffffffu, s1, 16);
        float k = b3 ? k1 : k0, s = b3 ? k0 : k1;
        k += __shfl_xor_sync(0xffffffffu, s, 8);
        k += __shfl_xor_sync(0xffffffffu, k, 4);
        k += __shfl_xor_sync(0xffffffffu, k, 2);
        k += __shfl_xor_sync(0xffffffffu, k, 1);
        if ((lane & 7) == 0) P.out[fb * 512 + fcol] = __float2bfloat16_rn(k + xres);
        if (tid == 0) STAMP(25);
    }
}

typedef CUresult (*PFN_encodeTiled)(CUtensorMap*, CUtensorMapDataType, cuuint32_t, void*, const cuuint64_t*, const cuuint64_t*,
                                    const cuuint32_t*, const cuuint32_t*, CUtensorMapInterleave, CUtensorMapSwizzle,
                                    CUtensorMapL2promotion, CUtensorMapFloatOOBfill);

void make_map(PFN_encodeTiled enc, CUtensorMap* m, const void* ptr, int rank, const cuuint64_t* dims, const cuuint64_t* strides,
              const cuuint32_t* box) {
    cuuint32_t es[3] = {1, 1, 1};
    enc(m, CU_TENSOR_MAP_DATA_TYPE_BFLOAT16, rank, const_cast<void*>(ptr), dims, strides, box, es,
        CU_TENSOR_MAP_INTERLEAVE_NONE, CU_TENSOR_MAP_SWIZZLE_128B, CU_TENSOR_MAP_L2_PROMOTION_NONE, CU_TENSOR_MAP_FLOAT_OOB_FILL_NONE);
}
void make_map2(PFN_encodeTiled enc, CUtensorMap* m, const void* ptr, uint64_t rows, uint64_t cols, uint32_t boxc, uint32_t boxr) {
    cuuint64_t dims[2] = {cols, rows}; cuuint64_t strides[1] = {cols * 2}; cuuint32_t box[2] = {boxc, boxr};
    make_map(enc, m, ptr, 2, dims, strides, box);
}

Tune g_tune = { 128.f / 3300.f, 0, 8192, -1, -1, -1, -1, -1, -1, -1, 160, 300, 400, 100, 100, 50, 400, 1 };

}

extern "C" void kernel_launch(void* const* d_in, const int* in_sizes, int n_in, void* d_out, int out_size) {
    (void)in_sizes; (void)n_in; (void)out_size;
    static PFN_encodeTiled enc = nullptr;
    if (!enc) {
        void* fn = nullptr; cudaDriverEntryPointQueryResult qr;
        cudaGetDriverEntryPoint("cuTensorMapEncodeTiled", &fn, cudaEnableDefault, &qr);
        enc = (PFN_encodeTiled)fn;
        cudaFuncSetAttribute(mla_glu_kernel, cudaFuncAttributeMaxDynamicSharedMemorySize, SMEM_BYTES);
    }
    Params P;
    P.x = (const __nv_bfloat16*)d_in[0];
    P.out = (__nv_bfloat16*)d_out;
    static Scratch* scratch = nullptr;
    if (!scratch) cudaGetSymbolAddress((void**)&scratch, g_scratch);
    P.sc = scratch;
    P.p_wq = (const char*)d_in[2]; P.p_wuk = (const char*)d_in[3]; P.p_wuv = (const char*)d_in[4];
    P.p_wo = (const char*)d_in[5];  P.p_wg = (const char*)d_in[7]; P.p_wu = (const char*)d_in[8];  P.p_wd = (const char*)d_in[9];
    make_map2(enc, &P.wq,  d_in[2], 512, 4096, 64, 128);
    make_map2(enc, &P.wuk, d_in[3], 512, 4096, 64, 128);
    {
        cuuint64_t dims[3] = {4096, 64, 8}; cuuint64_t strides[2] = {8192, 64 * 8192}; cuuint32_t box[3] = {64, 16, 8};
        make_map(enc, &P.wuv, d_in[4], 3, dims, strides, box);
    }
    make_map2(enc, &P.wo,  d_in[5], 4096, 512, 64, 128);
    make_map2(enc, &P.ckv, d_in[1], 8192, 512, 64, 64);
    make_map2(enc, &P.wg,  d_in[7], 512, 1376, 64, 128);
    make_map2(enc, &P.wu,  d_in[8], 512, 1376, 64, 128);
    make_map2(enc, &P.wd,  d_in[9], 1376, 512, 64, 48);
    P.tune = g_tune;
    mla_glu_kernel<<<NCTA, NTHREADS, SMEM_BYTES, cudaStreamPerThread>>>(P);
}
```

```cpp
#include <cuda_runtime.h>
#include <cuda_bf16.h>
#include <cuda.h>
#include <stdint.h>

namespace {

constexpr int NCTA     = 128;
constexpr int NTHREADS = 352;
constexpr int SPIN_LIMIT = 1 << 22;
constexpr int NGLU     = 43;

constexpr uint32_t OFF_RA  = 0;
constexpr uint32_t OFF_RB  = 65536;
constexpr uint32_t OFF_R0  = 131072;
constexpr uint32_t OFF_GU  = OFF_RB + 32768;
constexpr uint32_t OFF_R1  = 163840;
constexpr uint32_t OFF_QA  = 196608;
constexpr uint32_t OFF_XN  = 212992;
constexpr uint32_t OFF_Y   = OFF_XN + 2048;
constexpr uint32_t OP_Q = 0, OP_CL = 32, OP_CX = 64, OP_H = 96;
constexpr uint32_t OFF_P0  = OFF_Y + 2048 + 128;
constexpr uint32_t OFF_P1  = OFF_P0 + 2048;
constexpr uint32_t OFF_PA  = OFF_P1 + 2048;
constexpr uint32_t OFF_PG  = OFF_PA + 2048;
constexpr uint32_t OFF_ST  = OFF_PG + 2048;
constexpr uint32_t ST_WMAX = 0;
constexpr uint32_t ST_LSUM = 512;
constexpr uint32_t ST_M0   = 1024;
constexpr uint32_t ST_M1   = 1088;
constexpr uint32_t ST_STG  = 1280;
constexpr uint32_t OFF_BAR = OFF_ST + 1792;
constexpr uint32_t OFF_T0  = OFF_BAR + 256;
constexpr uint32_t OFF_STAMP = OFF_BAR + 512;
constexpr uint32_t SMEM_USED = OFF_STAMP + 1024;
constexpr uint32_t SMEM_BYTES = SMEM_USED + 1024;
static_assert(SMEM_BYTES <= 232448, "smem");
static_assert((OFF_P0 % 128) == 0 && (OFF_PA % 16) == 0 && (OFF_ST % 16) == 0 && (OFF_BAR % 8) == 0, "align");

enum { B_WQ = 0  , B_WUK = 4, B_CKV = 5  , B_G1 = 9, B_WUV = 10, B_WO = 11  , B_WD = 15,
       B_XA = 16, B_XG = 17, B_XD = 18,
       B_INIT2 = 19, B_EVX2 = 13, B_EVST = 14,
       B_FREEA = 20, B_FREE1 = 21, B_FREEB = 22, B_FREEQ = 23, B_EVX1 = 24, B_T0 = 25, NBARS = 26 };
static_assert(NBARS * 8 <= 256, "bars");

struct Ent { signed char grp, kind, s0, s1; short t, dt; };
enum { G_WUK = 0, G_CKV0, G_CKV1, G_WO01, G_WO23, G_WUV, G_GU, G_WD, G_END };
struct Tune {
    int   bo_1, bo_2, bo_4;
    int   dl_1, dl_2;
    int   mode;
    int   t_init2;
    int   dt_init2;
    int   stag;
    Ent   la[14], lb[14];
};

struct Scratch {
    uint4 X2[128 * 64 * 16];
    uint4 X4[64 * 256];
    uint4 X1[2 * 32 * 64];
    uint4 XS[32 * 64 * 2];
    unsigned epoch[NCTA * 8];
};

struct Params {
    const __nv_bfloat16* x;
    Scratch* sc;
    __nv_bfloat16* out;
    Tune tune;
    alignas(64) CUtensorMap wq, wuk, ckv, wg, wu, wuv, wo, wd;
};

__device__ Scratch g_scratch;
#define STAMP(i) do {} while (0)
#define STAMPW(i) do {} while (0)
__device__ __forceinline__ uint32_t smem_u32(const void* p) { return (uint32_t)__cvta_generic_to_shared(p); }
__device__ __forceinline__ unsigned long long gtime() {
    unsigned long long t; asm volatile("mov.u64 %0, %%globaltimer;" : "=l"(t)); return t;
}
__device__ __forceinline__ void mbar_init(uint32_t bar, uint32_t cnt) {
    asm volatile("mbarrier.init.shared::cta.b64 [%0], %1;" :: "r"(bar), "r"(cnt) : "memory");
}
__device__ __forceinline__ void mbar_expect_tx(uint32_t bar, uint32_t bytes) {
    asm volatile("mbarrier.arrive.expect_tx.shared::cta.b64 _, [%0], %1;" :: "r"(bar), "r"(bytes) : "memory");
}
__device__ __forceinline__ void mbar_arrive(uint32_t bar) {
    asm volatile("mbarrier.arrive.shared::cta.b64 _, [%0];" :: "r"(bar) : "memory");
}
__device__ __forceinline__ void mbar_wait(uint32_t bar, uint32_t parity) {
    uint32_t done; int it = 0;
    do {
        asm volatile("{\n.reg .pred p;\nmbarrier.try_wait.parity.shared::cta.b64 p, [%1], %2;\nselp.u32 %0, 1, 0, p;\n}"
                     : "=r"(done) : "r"(bar), "r"(parity) : "memory");
    } while (!done && ++it < SPIN_LIMIT);
    if (!done) __trap();
}
__device__ __forceinline__ void tma2d(uint32_t dst, const CUtensorMap* m, int c0, int c1, uint32_t bar) {
    asm volatile("cp.async.bulk.tensor.2d.shared::cluster.global.mbarrier::complete_tx::bytes [%0], [%1, {%3,%4}], [%2];"
                 :: "r"(dst), "l"(m), "r"(bar), "r"(c0), "r"(c1) : "memory");
}
__device__ __forceinline__ void tma3d(uint32_t dst, const CUtensorMap* m, int c0, int c1, int c2, uint32_t bar) {
    asm volatile("cp.async.bulk.tensor.3d.shared::cluster.global.mbarrier::complete_tx::bytes [%0], [%1, {%3,%4,%5}], [%2];"
                 :: "r"(dst), "l"(m), "r"(bar), "r"(c0), "r"(c1), "r"(c2) : "memory");
}
__device__ __forceinline__ void tma2d_pf(const CUtensorMap* m, int c0, int c1) {
    asm volatile("cp.async.bulk.prefetch.tensor.2d.L2.global.tile [%0, {%1,%2}];" :: "l"(m), "r"(c0), "r"(c1) : "memory");
}
__device__ __forceinline__ void tma3d_pf(const CUtensorMap* m, int c0, int c1, int c2) {
    asm volatile("cp.async.bulk.prefetch.tensor.3d.L2.global.tile [%0, {%1,%2,%3}];" :: "l"(m), "r"(c0), "r"(c1), "r"(c2) : "memory");
}
__device__ __forceinline__ void bulk_pf(const void* src, uint32_t bytes) {
    asm volatile("cp.async.bulk.prefetch.L2.global [%0], %1;" :: "l"(src), "r"(bytes) : "memory");
}
__device__ __forceinline__ void pf_map(const CUtensorMap* m) {
    asm volatile("prefetch.tensormap [%0];" :: "l"(m) : "memory");
}
__device__ __forceinline__ void bar_sync(int id, int n) { asm volatile("bar.sync %0, %1;" :: "r"(id), "r"(n) : "memory"); }
__device__ __forceinline__ void bar_arrive(int id, int n) { asm volatile("bar.arrive %0, %1;" :: "r"(id), "r"(n) : "memory"); }
__device__ __forceinline__ void fence_async() { asm volatile("fence.proxy.async.shared::cta;" ::: "memory"); }

__device__ __forceinline__ void st_ll(uint4* p, uint32_t a, uint32_t b, uint32_t c, uint32_t d) {
    asm volatile("{\n.reg .b128 t;\nmov.b128 t, {%1,%2,%3,%4};\nst.relaxed.gpu.global.b128 [%0], t;\n}"
                 :: "l"(p), "r"(a), "r"(b), "r"(c), "r"(d) : "memory");
}
__device__ __forceinline__ uint4 ld_ll(const uint4* p) {
    uint4 v;
    asm volatile("{\n.reg .b128 t;\nld.relaxed.gpu.global.b128 t, [%4];\nmov.b128 {%0,%1,%2,%3}, t;\n}"
                 : "=r"(v.x), "=r"(v.y), "=r"(v.z), "=r"(v.w) : "l"(p) : "memory");
    return v;
}
__device__ __forceinline__ void spin_clk(int n) {
    uint32_t c0, c; asm volatile("mov.u32 %0, %%clock;" : "=r"(c0));
    do { asm volatile("mov.u32 %0, %%clock;" : "=r"(c)); } while ((int)(c - c0) < n);
}
__device__ __forceinline__ uint4 poll_ll(const uint4* p, uint32_t tag, int backoff) {
    uint4 v = ld_ll(p); int it = 0;
    while (((v.x ^ tag) & 1u) && ++it < SPIN_LIMIT) { spin_clk(backoff); v = ld_ll(p); }
    if ((v.x ^ tag) & 1u) __trap();
    v.x &= ~1u;
    return v;
}
template <int N>
__device__ __forceinline__ void poll_ll_n(uint4 (&v)[N], const uint4* p, int stride, uint32_t tag, int backoff) {
    uint32_t pend = 0; int it = 0;
#pragma unroll
    for (int i = 0; i < N; i++) v[i] = ld_ll(p + i * stride);
#pragma unroll
    for (int i = 0; i < N; i++) if ((v[i].x ^ tag) & 1u) pend |= 1u << i;
    while (pend && ++it < SPIN_LIMIT) {
        spin_clk(backoff);
#pragma unroll
        for (int i = 0; i < N; i++) if (pend & (1u << i)) v[i] = ld_ll(p + i * stride);
#pragma unroll
        for (int i = 0; i < N; i++) if (!((v[i].x ^ tag) & 1u)) pend &= ~(1u << i);
    }
    if (pend) __trap();
#pragma unroll
    for (int i = 0; i < N; i++) v[i].x &= ~1u;
}

__device__ __forceinline__ uint64_t mk_desc(uint32_t sa16, uint32_t lbo, uint32_t sbo, uint32_t swz) {
    const uint32_t lo = sa16 + ((lbo >> 4) << 16);
    const uint32_t hi = (sbo >> 4) | (swz << 30);
    return ((uint64_t)hi << 32) | lo;
}
__device__ __forceinline__ void wg_fence()  { asm volatile("wgmma.fence.sync.aligned;" ::: "memory"); }
__device__ __forceinline__ void wg_commit() { asm volatile("wgmma.commit_group.sync.aligned;" ::: "memory"); }
template <int N> __device__ __forceinline__ void wg_wait() { asm volatile("wgmma.wait_group.sync.aligned %0;" :: "n"(N) : "memory"); }

template <int TA, int TB>
__device__ __forceinline__ void mma_n8(float (&d)[4], uint64_t da, uint64_t db, int acc) {
    asm volatile("{\n.reg .pred p;\nsetp.ne.b32 p, %6, 0;\n"
                 "wgmma.mma_async.sync.aligned.m64n8k16.f32.bf16.bf16 {%0,%1,%2,%3}, %4, %5, p, 1, 1, %7, %8;\n}\n"
                 : "+f"(d[0]), "+f"(d[1]), "+f"(d[2]), "+f"(d[3])
                 : "l"(da), "l"(db), "r"(acc), "n"(TA), "n"(TB));
}
template <int TA, int TB>
__device__ __forceinline__ void mma_n16(float (&d)[8], uint64_t da, uint64_t db, int acc) {
    asm volatile("{\n.reg .pred p;\nsetp.ne.b32 p, %10, 0;\n"
                 "wgmma.mma_async.sync.aligned.m64n16k16.f32.bf16.bf16 {%0,%1,%2,%3,%4,%5,%6,%7}, %8, %9, p, 1, 1, %11, %12;\n}\n"
                 : "+f"(d[0]), "+f"(d[1]), "+f"(d[2]), "+f"(d[3]), "+f"(d[4]), "+f"(d[5]), "+f"(d[6]), "+f"(d[7])
                 : "l"(da), "l"(db), "r"(acc), "n"(TA), "n"(TB));
}

__device__ __forceinline__ float bf_round(float v) { return __bfloat162float(__float2bfloat16_rn(v)); }
__device__ __forceinline__ uint32_t pack_bf(float lo, float hi) {
    uint32_t r; asm("cvt.rn.bf16x2.f32 %0, %1, %2;" : "=r"(r) : "f"(hi), "f"(lo)); return r;
}
__device__ __forceinline__ float bf_lo(uint32_t w) { return __uint_as_float(w << 16); }
__device__ __forceinline__ float bf_hi(uint32_t w) { return __uint_as_float(w & 0xFFFF0000u); }
__device__ __forceinline__ float ex2(float v) { float r; asm("ex2.approx.ftz.f32 %0, %1;" : "=f"(r) : "f"(v)); return r; }
__device__ __forceinline__ void sts16(uint32_t a, float v) {
    unsigned short s = __bfloat16_as_ushort(__float2bfloat16_rn(v));
    asm volatile("st.shared.u16 [%0], %1;" :: "r"(a), "h"(s) : "memory");
}
__device__ __forceinline__ void sts32(uint32_t a, uint32_t v) { asm volatile("st.shared.u32 [%0], %1;" :: "r"(a), "r"(v) : "memory"); }
__device__ __forceinline__ void stsf(uint32_t a, float v) { asm volatile("st.shared.f32 [%0], %1;" :: "r"(a), "f"(v) : "memory"); }
__device__ __forceinline__ float ldsf(uint32_t a) { float v; asm volatile("ld.shared.f32 %0, [%1];" : "=f"(v) : "r"(a) : "memory"); return v; }
__device__ __forceinline__ float4 ldsf4(uint32_t a) {
    float4 v; asm volatile("ld.shared.v4.f32 {%0,%1,%2,%3}, [%4];" : "=f"(v.x), "=f"(v.y), "=f"(v.z), "=f"(v.w) : "r"(a) : "memory"); return v;
}
__device__ __forceinline__ void wait_until(unsigned long long t) { while (gtime() < t) {} }

__device__ __forceinline__ uint32_t mapa(uint32_t addr, uint32_t rank) {
    uint32_t r; asm("mapa.shared::cluster.u32 %0, %1, %2;" : "=r"(r) : "r"(addr), "r"(rank)); return r;
}
__device__ __forceinline__ void st_async4(uint32_t dst, const float (&v)[4], uint32_t bar) {
    asm volatile("st.async.weak.shared::cluster.mbarrier::complete_tx::bytes.v4.f32 [%0], {%1,%2,%3,%4}, [%5];"
                 :: "r"(dst), "f"(v[0]), "f"(v[1]), "f"(v[2]), "f"(v[3]), "r"(bar) : "memory");
}
__device__ __forceinline__ void mbar_wait_cluster(uint32_t bar, uint32_t parity) {
    uint32_t done; int it = 0;
    do {
        asm volatile("{\n.reg .pred p;\nmbarrier.try_wait.parity.acquire.cluster.shared::cta.b64 p, [%1], %2;\nselp.u32 %0, 1, 0, p;\n}"
                     : "=r"(done) : "r"(bar), "r"(parity) : "memory");
    } while (!done && ++it < SPIN_LIMIT);
    if (!done) __trap();
}

__device__ __forceinline__ void gemv_mmajor(float (&acc)[4], uint32_t a_base, uint32_t b_base, int ks0, int ks1, int first_acc) {
#pragma unroll
    for (int ks = 0; ks < 8; ks++) {
        if (ks >= ks0 && ks < ks1)
            mma_n8<1, 0>(acc, mk_desc(a_base + ks * 128, 1024, 1024, 1), mk_desc(b_base + ks * 16, 128, 128, 0), (ks > ks0) | first_acc);
    }
}

__global__ void __cluster_dims__(2, 1, 1) __launch_bounds__(NTHREADS, 1)
mla_glu_kernel(const __grid_constant__ Params P)
{
    extern __shared__ uint8_t smem_raw[];
    const int tid = threadIdx.x, lane = tid & 31;
    const int bid = blockIdx.x;
    const unsigned long long t0 = gtime();
    uint4 xa, xb; float x0 = 0.f;
    if ((tid & 127) < 32 && tid < 256) {
        const __nv_bfloat16* xr = P.x + (tid >> 7) * 512;
        const uint4* xp = reinterpret_cast<const uint4*>(xr + lane * 16);
        xa = xp[0]; xb = xp[1];
        x0 = __bfloat162float(xr[0]);
    }
    const uint32_t sb = (smem_u32(smem_raw) + 1023u) & ~1023u;
    const uint32_t bars = sb + OFF_BAR;
    auto BAR = [&](int i) { return bars + 8u * i; };
    const int h = bid >> 2, j = bid & 3;
    const int pr = bid >> 1, r = bid & 1;
    if (tid == 288) {
#pragma unroll
        for (int i = 0; i < 4; i++) mbar_init(BAR(B_WQ + i), 1);
        asm volatile("fence.mbarrier_init.release.cluster;" ::: "memory");
#pragma unroll
        for (int i = 0; i < 4; i++) {
            mbar_expect_tx(BAR(B_WQ + i), 16384);
            tma2d(sb + OFF_RA + i * 16384, &P.wq, h * 128 + r * 64, i * 128, BAR(B_WQ + i));
        }
        STAMP(29);
#pragma unroll
        for (int i = 4; i < NBARS; i++) mbar_init(BAR(i), (i == B_EVST || i == B_EVX1) ? 8 : (i >= B_FREEA && i <= B_FREEQ) ? 2 : 1);
        mbar_expect_tx(BAR(B_T0), 8); mbar_expect_tx(BAR(B_XA), 2048); mbar_expect_tx(BAR(B_XG), 2048); mbar_expect_tx(BAR(B_XD), 2048);
        asm volatile("fence.mbarrier_init.release.cluster;" ::: "memory");
        fence_async();
    }
    __syncwarp();
    asm volatile("barrier.cluster.arrive.relaxed.aligned;" ::: "memory");
    const int warp = __shfl_sync(0xffffffffu, tid >> 5, 0);
    const uint32_t sd = (sb & 0x3FFFFu) >> 4;
    const bool glu = pr < NGLU;
    Scratch* const sc = P.sc;

    if (warp >= 8) {
      if (warp == 9 || warp == 8) {
        bar_arrive(0, NTHREADS);
        asm volatile("barrier.cluster.wait.acquire.aligned;" ::: "memory");
        if (lane == 0) {
            unsigned long long tp;
            if (warp == 8 && r == 0) {
#pragma unroll
                for (int i = 0; i < 2; i++)
                    asm volatile("st.async.weak.shared::cluster.mbarrier::complete_tx::bytes.b64 [%0], %1, [%2];"
                                 :: "r"(mapa(sb + OFF_T0, i)), "l"(t0), "r"(mapa(BAR(B_T0), i)) : "memory");
            }
            mbar_wait_cluster(BAR(B_T0), 0);
            asm volatile("ld.shared.u64 %0, [%1];" : "=l"(tp) : "r"(sb + OFF_T0) : "memory");
            if (P.tune.mode & 64) tp = t0;
            if (warp == 9) { pf_map(&P.wuk); pf_map(&P.ckv); pf_map(&P.wg); pf_map(&P.wu); pf_map(&P.wuv); pf_map(&P.wo); pf_map(&P.wd); }
            const Ent* list = (warp == 9) ? P.tune.la : P.tune.lb;
            const unsigned long long tb = tp + (((pr * 11) & 31) * P.tune.stag >> 5);
#pragma unroll 1
            for (int e = 0; e < 14; e++) {
                const Ent E = list[e];
                if (E.grp >= G_END) break;
                if (E.grp >= G_GU && !glu) continue;
                const bool pf = E.kind != 0;
                unsigned long long tn;
                if (E.t == -2) mbar_wait(BAR(B_EVX2), 0);
                if (E.t == -3) mbar_wait(BAR(B_EVST), 0);
                if (E.t == -4) mbar_wait(BAR(B_EVX1), 0);
                if (E.t >= 0) tn = tb + E.t; else tn = gtime();
                const int dt = E.dt;
                bool first = true;
                auto step = [&]() { if (first || dt) wait_until(tn); first = false; tn += dt; };
                const int s0 = E.s0, s1 = E.s1;
                switch (E.grp) {
                case G_WUK:
                    if (!pf && s0 == 0) mbar_expect_tx(BAR(B_WUK), 32768);
#pragma unroll 1
                    for (int i = s0; i < s1; i++) {
                        step();
                        if (pf) { tma2d_pf(&P.wuk, h * 128, j * 128 + i * 32); tma2d_pf(&P.wuk, h * 128 + 64, j * 128 + i * 32); }
                        else {
                            tma2d(sb + OFF_R1 + i * 4096,         &P.wuk, h * 128,      j * 128 + i * 32, BAR(B_WUK));
                            tma2d(sb + OFF_R1 + 16384 + i * 4096, &P.wuk, h * 128 + 64, j * 128 + i * 32, BAR(B_WUK));
                        }
                    }
                    break;
                case G_CKV0: case G_CKV1: {
                    const int t = E.grp - G_CKV0;
                    if (!pf && t) mbar_wait(BAR(B_FREEA), 0);
#pragma unroll 1
                    for (int k = s0; k < s1; k++) {
                        const int ps = k >> 1, rh = k & 1;
                        step();
                        if (pf) {
#pragma unroll
                            for (int u = 0; u < 2; u++) tma2d_pf(&P.ckv, (ps * 4 + r * 2 + u) * 64, pr * 128 + t * 64 + rh * 32);
                        } else {
                            if (!rh) mbar_expect_tx(BAR(B_CKV + t * 2 + ps), 32768);
#pragma unroll
                            for (int u = 0; u < 4; u++)
                                tma2d(sb + (t ? OFF_RA : OFF_RB) + (ps * 4 + u) * 8192 + rh * 4096, &P.ckv, (ps * 4 + u) * 64, pr * 128 + t * 64 + rh * 32,
                                      BAR(B_CKV + t * 2 + ps));
                        }
                    }
                    break; }
                case G_WO01: case G_WO23: {
                    const int t = E.grp - G_WO01;
                    if (!pf) { if (t) mbar_wait(BAR(B_FREE1), 0); if (s0 == 0) mbar_expect_tx(BAR(B_WO + t), 32768); }
#pragma unroll 1
                    for (int kq = s0; kq < s1; kq++) {
                        step();
                        if (pf) tma2d_pf(&P.wo, r * 256 + t * 128 + (pr & 1) * 64, h * 128 + kq * 32);
                        else {
                            tma2d(sb + (t ? OFF_R1 : OFF_R0) + kq * 4096,         &P.wo, r * 256 + t * 128,      h * 128 + kq * 32, BAR(B_WO + t));
                            tma2d(sb + (t ? OFF_R1 : OFF_R0) + 16384 + kq * 4096, &P.wo, r * 256 + t * 128 + 64, h * 128 + kq * 32, BAR(B_WO + t));
                        }
                    }
                    break; }
                case G_WUV:
                    if (!pf) { mbar_wait(BAR(B_FREEB), 0); if (s0 == 0) mbar_expect_tx(BAR(B_WUV), 32768); }
#pragma unroll 1
                    for (int i = s0; i < s1; i++) {
                        step();
                        if (pf) { tma3d_pf(&P.wuv, h * 128, j * 16, i * 2); tma3d_pf(&P.wuv, h * 128 + 64, j * 16, i * 2); }
                        else {
                            tma3d(sb + OFF_RB + i * 4096,         &P.wuv, h * 128,      j * 16, i * 2, BAR(B_WUV));
                            tma3d(sb + OFF_RB + 16384 + i * 4096, &P.wuv, h * 128 + 64, j * 16, i * 2, BAR(B_WUV));
                        }
                    }
                    break;
                case G_GU:
                    if (!pf) { mbar_wait(BAR(B_FREEB), 0); if (s0 == 0) mbar_expect_tx(BAR(B_G1), 32768); }
#pragma unroll 1
                    for (int i = s0; i < s1; i++) {
                        step();
                        if (pf) tma2d_pf((i & 1) ? &P.wu : &P.wg, pr * 32, (2 * r + (i >> 1)) * 128);
                        else tma2d(sb + OFF_GU + i * 8192, (i & 1) ? &P.wu : &P.wg, pr * 32, (2 * r + (i >> 1)) * 128, BAR(B_G1));
                    }
                    break;
                default:
                    if (!pf) { mbar_wait(BAR(B_FREEQ), 0); if (s0 == 0) mbar_expect_tx(BAR(B_WD), 16384); }
#pragma unroll 1
                    for (int i = s0; i < s1; i++) {
                        step();
                        if (pf) tma2d_pf(&P.wd, r * 256 + i * 64, pr * 32);
                        else tma2d(sb + OFF_QA + i * 4096, &P.wd, r * 256 + i * 64, pr * 32, BAR(B_WD));
                    }
                    break;
                }
                STAMP(128 + (warp == 8) * 16 + e);
            }
            STAMP(35 - (warp == 8));
        }
      } else if (warp == 10) {
        const uint32_t ntag = sc->epoch[bid * 8] & 1u;
        if (ntag < 2 && lane == 0) STAMP(26);
        st_ll(sc->X1 + ((lane >> 4) * 32 + h) * 64 + 16 * j + (lane & 15), ntag, 0, 0, 0);
        st_ll(sc->XS + ((16 * r + (lane >> 1)) * 64 + pr) * 2 + (lane & 1), ntag, 0, 0, 0);
#pragma unroll
        for (int i = 0; i < 4; i++) st_ll(sc->X4 + pr * 256 + r * 128 + i * 32 + lane, ntag, 0, 0, 0);
        bar_sync(0, NTHREADS);
        uint4* px2 = sc->X2 + ((size_t)((16 * r) * 4 + (lane >> 4)) * 64 + pr) * 16 + (lane & 15);
        if (!(P.tune.mode & 1)) {
            unsigned long long tn = t0 + P.tune.t_init2;
#pragma unroll 1
            for (int i = 0; i < 32; i++) {
                wait_until(tn); tn += P.tune.dt_init2;
                st_ll(px2 + i * (2 * 64 * 16), ntag, 0, 0, 0);
            }
        }
        __syncwarp();
        asm volatile("fence.acq_rel.cta;" ::: "memory");
        if (lane == 0) { mbar_arrive(BAR(B_INIT2)); STAMP(27); }
      }
      return;
    }

    const int g  = warp >> 2;
    const int w  = warp & 3;
    const int tg = tid & 127;
    const int rr = lane >> 2, q = lane & 3;
    const Tune& T = P.tune;

    if (tid == 0) STAMP(36);
    const unsigned ep = sc->epoch[bid * 8];
    const int fcc = 2 * bid + (warp & 1);
    const int fcol = 256 * (fcc >> 7) + 64 * ((fcc >> 5) & 3) + 16 * ((fcc >> 3) & 3) + (fcc & 7) + 8 * (lane >> 4);
    const int fb = (lane >> 3) & 1;
    float xres = 0.f;
    if (w == 0) {
        const uint32_t xw[8] = { xa.x, xa.y, xa.z, xa.w, xb.x, xb.y, xb.z, xb.w };
        float xv[16];
#pragma unroll
        for (int i = 0; i < 8; i++) { xv[2 * i] = bf_lo(xw[i]); xv[2 * i + 1] = bf_hi(xw[i]); }
        float s = 0.f, s2 = 0.f;
#pragma unroll
        for (int i = 0; i < 16; i++) { const float d = xv[i] - x0; s += d; s2 = fmaf(d, d, s2); }
        if (tid == 0 && s != 12345.f) STAMP(28);
#pragma unroll
        for (int o = 16; o; o >>= 1) { s += __shfl_xor_sync(0xffffffffu, s, o); s2 += __shfl_xor_sync(0xffffffffu, s2, o); }
        const float md = s * (1.0f / 512.0f);
        const float var = fmaxf(fmaf(-md, md, s2 * (1.0f / 512.0f)), 0.f);
        const float mb = bf_round(x0 + md);
        const float rs = __frcp_rn(bf_round(__fsqrt_rn(bf_round(bf_round(var) + 1e-5f))));
        uint32_t o[8];
#pragma unroll
        for (int i = 0; i < 8; i++) o[i] = pack_bf(bf_round(xv[2 * i] - mb) * rs, bf_round(xv[2 * i + 1] - mb) * rs);
        const uint32_t a = sb + OFF_XN + (lane >> 3) * 32 + (lane & 7) * 256 + g * 16;
        asm volatile("st.shared.v4.u32 [%0], {%1,%2,%3,%4};" :: "r"(a), "r"(o[0]), "r"(o[1]), "r"(o[2]), "r"(o[3]) : "memory");
        asm volatile("st.shared.v4.u32 [%0], {%1,%2,%3,%4};" :: "r"(a + 128), "r"(o[4]), "r"(o[5]), "r"(o[6]), "r"(o[7]) : "memory");
        if (tid == 0) STAMP(30);
        fence_async();
    }
    if (warp < 2) xres = __bfloat162float(P.x[fb * 512 + fcol]);
    const uint32_t tag = (ep + 1u) & 1u;
    const uint32_t ch16 = (w * 8 + rr) * 16;
    const uint32_t own_sb = mapa(sb, r), peer_sb = mapa(sb, r ^ 1);

    bar_sync(0, NTHREADS);
    if (tid == 0) sc->epoch[bid * 8] = ep + 1u;
    if (tid == 0) { STAMP(0); }

    auto gather2 = [&](uint32_t buf, uint32_t op) {
        const int d = tid >> 1, b = tid & 1;
        const uint32_t a = buf + (d >> 6) * 1024 + (((d >> 4) & 3) * 8 + (d & 7)) * 16 + (((d >> 3) & 1) * 2 + b) * 4;
        sts16(op + (d >> 3) * 128 + b * 16 + (d & 7) * 2, ldsf(a) + ldsf(a + 512));
        fence_async();
    };

    float acc[4];
    mbar_wait(BAR(B_WQ + 2 * g), 0);
    wg_fence();
    gemv_mmajor(acc, sd + ((OFF_RA + 2 * g * 16384) >> 4), sd + ((OFF_XN + 2 * g * 32) >> 4), 0, 8, 0);
    wg_commit();
    mbar_wait(BAR(B_WQ + 2 * g + 1), 0);
    if (tid == 0) STAMP(1);
    wg_fence();
    gemv_mmajor(acc, sd + ((OFF_RA + (2 * g + 1) * 16384) >> 4), sd + ((OFF_XN + (2 * g + 1) * 32) >> 4), 0, 8, 1);
    wg_commit();
    asm volatile("barrier.cluster.wait.acquire.aligned;" ::: "memory");
    wg_wait<0>();
    if (tg == 0) mbar_arrive(BAR(B_FREEA));
    if (q == 0) {
        const uint32_t o = OFF_PA + r * 1024 + g * 512 + ch16;
        st_async4(own_sb + o, acc, own_sb + OFF_BAR + 8 * B_XA);
        st_async4(peer_sb + o, acc, peer_sb + OFF_BAR + 8 * B_XA);
    }
    if (tid == 0) STAMP(6);
    mbar_wait_cluster(BAR(B_XA), 0);
    if (tid == 0) STAMP(7);
    gather2(sb + OFF_PA, sb + OFF_Y + OP_Q);
    bar_sync(3, 256);
    if (tid == 0) STAMP(2);

    mbar_wait(BAR(B_WUK), 0);
    if (tid == 0) STAMP(3);
    wg_fence();
#pragma unroll
    for (int ks = 0; ks < 8; ks++)
        mma_n8<0, 0>(acc, mk_desc(sd + ((OFF_R1 + (ks >> 2) * 16384 + (ks & 3) * 32) >> 4) + g * 512, 16, 1024, 1),
                     mk_desc(sd + ((OFF_Y + OP_Q + ks * 256) >> 4), 128, 128, 0), ks > 0);
    wg_commit(); wg_wait<0>();
    if (tg == 0) mbar_arrive(BAR(B_FREE1));
    {
        const float qs = 0.08838834764831845f * 1.4426950408889634f;
        const uint32_t stg = sb + OFF_ST + ST_STG + warp * 64;
        if (q == 0) {
            sts16(stg + rr * 2,           acc[0] * qs);
            sts16(stg + 32 + rr * 2,      acc[1] * qs);
            sts16(stg + 16 + rr * 2,      acc[2] * qs);
            sts16(stg + 32 + 16 + rr * 2, acc[3] * qs);
        }
        __syncwarp();
        if (lane < 4) {
            uint4 v;
            asm volatile("ld.shared.v4.u32 {%0,%1,%2,%3}, [%4];" : "=r"(v.x), "=r"(v.y), "=r"(v.z), "=r"(v.w) : "r"(stg + lane * 16) : "memory");
            st_ll(sc->X1 + ((lane >> 1) * 32 + h) * 64 + 16 * j + 8 * g + 2 * w + (lane & 1), (v.x & ~1u) | tag, v.y, v.z, v.w);
        }
    }
    STAMPW(0);
    {
        const uint4* src = sc->X1 + ((pr >> 5) * 32 + 16 * r) * 64;
        uint4 v[4];
        spin_clk(T.dl_1);
        poll_ll_n<4>(v, src + tid, 256, tag, T.bo_1);
        __syncwarp();
        if (lane == 0) mbar_arrive(BAR(B_EVX1));
        STAMPW(1);
#pragma unroll
        for (int i = 0; i < 4; i++) {
            const int idx = i * 256 + tid, n = idx >> 6, kc = idx & 63;
            const uint32_t a = sb + OFF_QA + (kc >> 3) * 2048 + n * 128 + (((kc & 7) ^ (n & 7)) << 4);
            asm volatile("st.shared.v4.u32 [%0], {%1,%2,%3,%4};" :: "r"(a), "r"(v[i].x), "r"(v[i].y), "r"(v[i].z), "r"(v[i].w) : "memory");
        }
        fence_async();
    }
    bar_sync(3, 256);
    if (tid == 0) STAMP(5);

    float o[4][8];
    float pr8[8];
    const uint32_t st = sb + OFF_ST;
    {
        float s[8];
        const uint32_t tile = sd + ((g ? OFF_RA : OFF_RB) >> 4);
        if (g == 1) bar_sync(6, 256);
#pragma unroll
        for (int u = 0; u < 8; u++) {
            if ((u & 3) == 0) mbar_wait(BAR(B_CKV + g * 2 + (u >> 2)), 0);
            wg_fence();
#pragma unroll
            for (int ks = 0; ks < 4; ks++)
                mma_n16<0, 0>(s, mk_desc(tile + ((u * 8192 + ks * 32) >> 4), 16, 1024, 1),
                              mk_desc(sd + ((OFF_QA + u * 2048 + ks * 32) >> 4), 16, 1024, 1), (u | ks) != 0);
            wg_commit();
        }
        wg_wait<0>();
        if (g == 0) bar_arrive(6, 256);
        if (tg == 0) mbar_arrive(BAR(B_FREEQ));
        if (tg == 0) STAMP(8 + g * 4);
        float m[4];
#pragma unroll
        for (int i = 0; i < 4; i++) {
            m[i] = fmaxf(s[(i >> 1) * 4 + (i & 1)], s[(i >> 1) * 4 + (i & 1) + 2]);
#pragma unroll
            for (int x = 4; x < 32; x <<= 1) m[i] = fmaxf(m[i], __shfl_xor_sync(0xffffffffu, m[i], x));
        }
        const uint32_t wm = st + ST_WMAX + g * 256;
        if (rr == 0) {
#pragma unroll
            for (int i = 0; i < 4; i++) stsf(wm + (((i >> 1) * 8 + 2 * q + (i & 1)) * 4 + w) * 4, m[i]);
        }
        if (g == 1) {
            bar_sync(7, 256);
            wg_fence();
#pragma unroll
            for (int mt = 0; mt < 4; mt++)
#pragma unroll
                for (int ks = 0; ks < 4; ks++)
                    mma_n16<1, 1>(o[mt], mk_desc(sd + ((OFF_RB + (4 + mt) * 8192 + ks * 2048) >> 4), 1024, 1024, 1),
                                  mk_desc(sd + (OFF_P0 >> 4) + ks * 32, 256, 128, 0), ks > 0);
            wg_commit();
        }
        bar_sync(1 + g, 128);
#pragma unroll
        for (int i = 0; i < 4; i++) {
            const int col = (i >> 1) * 8 + 2 * q + (i & 1);
            float4 t4 = ldsf4(wm + col * 16);
            float mm = fmaxf(fmaxf(t4.x, t4.y), fmaxf(t4.z, t4.w));
            if (g) mm = fmaxf(mm, ldsf(st + ST_M0 + col * 4));
            m[i] = mm;
        }
#pragma unroll
        for (int i = 0; i < 8; i++) pr8[i] = ex2(s[i] - m[(i >> 2) * 2 + (i & 1)]);
        const uint32_t pb = sb + (g ? OFF_P1 : OFF_P0) + w * 512 + lane * 4;
        sts32(pb, pack_bf(pr8[0], pr8[1])); sts32(pb + 256, pack_bf(pr8[2], pr8[3]));
        sts32(pb + 128, pack_bf(pr8[4], pr8[5])); sts32(pb + 256 + 128, pack_bf(pr8[6], pr8[7]));
        if (rr == 0 && w == 0) {
#pragma unroll
            for (int i = 0; i < 4; i++) stsf(st + (g ? ST_M1 : ST_M0) + ((i >> 1) * 8 + 2 * q + (i & 1)) * 4, m[i]);
        }
        fence_async();
    }
    auto lsum = [&]() {
        float l[4];
#pragma unroll
        for (int i = 0; i < 4; i++) {
            l[i] = pr8[(i >> 1) * 4 + (i & 1)] + pr8[(i >> 1) * 4 + (i & 1) + 2];
#pragma unroll
            for (int x = 4; x < 32; x <<= 1) l[i] += __shfl_xor_sync(0xffffffffu, l[i], x);
        }
        if (rr == 0) {
#pragma unroll
            for (int i = 0; i < 4; i++) stsf(st + ST_LSUM + g * 256 + (((i >> 1) * 8 + 2 * q + (i & 1)) * 4 + w) * 4, l[i]);
        }
    };
    if (g == 0) {
        bar_arrive(7, 256);
        bar_sync(1, 128);
        if (tid == 0) STAMP(9);
        wg_fence();
#pragma unroll
        for (int mt = 0; mt < 4; mt++)
#pragma unroll
            for (int ks = 0; ks < 4; ks++)
                mma_n16<1, 1>(o[mt], mk_desc(sd + ((OFF_RB + mt * 8192 + ks * 2048) >> 4), 1024, 1024, 1),
                              mk_desc(sd + (OFF_P0 >> 4) + ks * 32, 256, 128, 0), ks > 0);
        wg_commit();
        lsum();
    }
    wg_wait<0>();
    if (tg == 0) mbar_arrive(BAR(B_FREEB));
    bar_sync(3, 256);
    if (tid == 0) STAMP(13);
    {
#pragma unroll
        for (int i = 0; i < 4; i++) {
            const int col = (i >> 1) * 8 + 2 * q + (i & 1);
            const float f = ex2(ldsf(st + ST_M0 + col * 4) - ldsf(st + ST_M1 + col * 4));
#pragma unroll
            for (int mt = 0; mt < 4; mt++) { o[mt][(i >> 1) * 4 + (i & 1)] *= f; o[mt][(i >> 1) * 4 + (i & 1) + 2] *= f; }
        }
    }
    if (g == 1) {
        lsum();
        bar_sync(2, 128);
        if (w == 0) {
            const int col = lane >> 1;
            const float m0 = ldsf(st + ST_M0 + col * 4), m1 = ldsf(st + ST_M1 + col * 4);
            const float4 a = ldsf4(st + ST_LSUM + col * 16), b = ldsf4(st + ST_LSUM + 256 + col * 16);
            const float l = ((a.x + a.y) + (a.z + a.w)) * ex2(m0 - m1) + ((b.x + b.y) + (b.z + b.w));
            st_ll(sc->XS + ((16 * r + (lane >> 1)) * 64 + pr) * 2 + (lane & 1), tag, __float_as_uint(m1), __float_as_uint(l), 0);
        }
        if (!(T.mode & 4)) bar_sync(6, 256);
    }
    wg_fence();
#pragma unroll
    for (int mt = 0; mt < 4; mt++)
#pragma unroll
        for (int ks = 0; ks < 4; ks++)
            mma_n16<1, 1>(o[mt], mk_desc(sd + ((OFF_RA + mt * 8192 + ks * 2048) >> 4) + g * 2048, 1024, 1024, 1),
                          mk_desc(sd + (OFF_P1 >> 4) + ks * 32, 256, 128, 0), 1);
    wg_commit();
    uint4* const pX2 = sc->X2 + ((size_t)((16 * r + 2 * q) * 4 + w) * 64 + pr) * 16 + g * 8 + rr;
    mbar_wait(BAR(B_INIT2), 0);
    wg_wait<0>();
    if (g == 0 && !(T.mode & 4)) bar_arrive(6, 256);
    if (tid == 0) STAMP(14);
#pragma unroll
    for (int ii = 0; ii < 4; ii++) {
        const int c0 = (ii >> 1) * 4 + (ii & 1);
        st_ll(pX2 + ((ii >> 1) * 8 + (ii & 1)) * (4 * 64 * 16),
              (pack_bf(o[0][c0], o[0][c0 + 2]) & ~1u) | tag, pack_bf(o[1][c0], o[1][c0 + 2]),
              pack_bf(o[2][c0], o[2][c0 + 2]), pack_bf(o[3][c0], o[3][c0 + 2]));
    }
    STAMPW(2);
    if (lane == 0) mbar_arrive(BAR(B_EVST));

    {
        const int ci = tg & 15, pg = tg >> 4;
        const uint4* src = sc->X2 + ((size_t)bid * 64 + 32 * g + pg) * 16 + ci;
        const uint4* ssrc = sc->XS + (h * 64 + 32 * g + lane) * 2;
        spin_clk(T.dl_2);
        uint4 dv[4], sv;
        sv = ld_ll(ssrc);
#pragma unroll
        for (int i = 0; i < 4; i++) dv[i] = ld_ll(src + i * 8 * 16);
        {
            uint32_t pend = ((sv.x ^ tag) & 1u) << 4;
#pragma unroll
            for (int i = 0; i < 4; i++) if ((dv[i].x ^ tag) & 1u) pend |= 1u << i;
            STAMPW(3);
            int it = 0;
            while (pend && ++it < SPIN_LIMIT) {
                spin_clk(T.bo_2);
                if (pend & 16u) sv = ld_ll(ssrc);
#pragma unroll
                for (int i = 0; i < 4; i++) if (pend & (1u << i)) dv[i] = ld_ll(src + i * 8 * 16);
                if (!((sv.x ^ tag) & 1u)) pend &= ~16u;
#pragma unroll
                for (int i = 0; i < 4; i++) if (!((dv[i].x ^ tag) & 1u)) pend &= ~(1u << i);
            }
            if (pend) __trap();
        }
        __syncwarp();
        STAMPW(4);
        if (tid == 0) mbar_arrive(BAR(B_EVX2));
        const float mp = __uint_as_float(sv.y), lp = __uint_as_float(sv.z);
        float M = mp;
#pragma unroll
        for (int x = 16; x; x >>= 1) M = fmaxf(M, __shfl_xor_sync(0xffffffffu, M, x));
        const float wp = ex2(mp - M);
        float L = wp * lp;
#pragma unroll
        for (int x = 16; x; x >>= 1) L += __shfl_xor_sync(0xffffffffu, L, x);
        float a8[8];
#pragma unroll
        for (int i = 0; i < 8; i++) a8[i] = 0.f;
#pragma unroll
        for (int i = 0; i < 4; i++) {
            uint4 v = dv[i]; v.x &= ~1u;
            const float wi = __shfl_sync(0xffffffffu, wp, i * 8 + pg);
            a8[0] += wi * bf_lo(v.x); a8[1] += wi * bf_hi(v.x); a8[2] += wi * bf_lo(v.y); a8[3] += wi * bf_hi(v.y);
            a8[4] += wi * bf_lo(v.z); a8[5] += wi * bf_hi(v.z); a8[6] += wi * bf_lo(v.w); a8[7] += wi * bf_hi(v.w);
        }
#pragma unroll
        for (int i = 0; i < 8; i++) a8[i] += __shfl_xor_sync(0xffffffffu, a8[i], 16);
        const uint32_t red = sb + OFF_P0 + g * 2048;
        if (lane < 16) {
            const uint32_t a = red + (w * 16 + ci) * 32;
            asm volatile("st.shared.v4.f32 [%0], {%1,%2,%3,%4};" :: "r"(a), "f"(a8[0]), "f"(a8[1]), "f"(a8[2]), "f"(a8[3]) : "memory");
            asm volatile("st.shared.v4.f32 [%0], {%1,%2,%3,%4};" :: "r"(a + 16), "f"(a8[4]), "f"(a8[5]), "f"(a8[6]), "f"(a8[7]) : "memory");
        }
        bar_sync(1 + g, 128);
        const int c2 = tg >> 3, e = tg & 7;
        const uint32_t a = red + c2 * 32 + e * 4;
        const float sum = (ldsf(a) + ldsf(a + 512)) + (ldsf(a + 1024) + ldsf(a + 1536));
        const int kg = ((c2 >> 3) * 4 + (e >> 1)) * 2 + (e & 1);
        sts16(sb + OFF_Y + OP_CL + kg * 128 + g * 16 + (c2 & 7) * 2, sum / L);
        fence_async();
    }
    bar_sync(3, 256);
    if (tid == 0) STAMP(16);

    mbar_wait(BAR(B_WUV), 0);
    if (tid == 0) STAMP(17);
    wg_fence();
    gemv_mmajor(acc, sd + (OFF_RB >> 4) + g * 1024, sd + ((OFF_Y + OP_CL) >> 4), 0, 8, 0);
    wg_commit(); wg_wait<0>();
    if (q == 0) {
        const uint32_t o2 = OFF_PA + g * 1024 + r * 512 + ch16;
        st_async4(own_sb + o2, acc, own_sb + OFF_BAR + 8 * B_XD);
        st_async4(peer_sb + o2, acc, peer_sb + OFF_BAR + 8 * B_XD);
    }
    if (tid == 0) STAMP(18);
    mbar_wait_cluster(BAR(B_XD), 0);
    gather2(sb + OFF_PA, sb + OFF_Y + OP_CX);
    bar_sync(3, 256);
    if (tid == 0) STAMP(21);

    if (glu) {
        mbar_wait(BAR(B_G1), 0);
        wg_fence();
#pragma unroll
        for (int ks = 0; ks < 8; ks++)
            mma_n8<1, 0>(acc, mk_desc(sd + ((OFF_GU + ks * 1024) >> 4) + g * 1024, 8192, 512, 2),
                         mk_desc(sd + ((OFF_XN + ks * 256) >> 4) + (2 * r + g) * 2, 128, 128, 0), ks > 0);
        wg_commit(); wg_wait<0>();
        if (q == 0) {
            const uint32_t o2 = OFF_PG + r * 1024 + g * 512 + ch16;
            st_async4(own_sb + o2, acc, own_sb + OFF_BAR + 8 * B_XG);
            st_async4(peer_sb + o2, acc, peer_sb + OFF_BAR + 8 * B_XG);
        }
    }
    if (tid == 0) STAMP(19);

    {
        float e0[4], e1[4];
        const uint32_t wot = sd + ((g ? OFF_R1 : OFF_R0) >> 4);
        mbar_wait(BAR(B_WO + g), 0);
        if (tid == 0) STAMP(22);
        wg_fence();
        gemv_mmajor(e0, wot,        sd + ((OFF_Y + OP_CX) >> 4), 0, 8, 0);
        gemv_mmajor(e1, wot + 1024, sd + ((OFF_Y + OP_CX) >> 4), 0, 8, 0);
        wg_commit();
        if (glu) {
            if (tid < 64) {
                mbar_wait_cluster(BAR(B_XG), 0);
                const int f = tid >> 1, b = tid & 1;
                const uint32_t a = sb + OFF_PG + ((f >> 4) * 8 + (f & 7)) * 16 + (((f >> 3) & 1) * 2 + b) * 4;
                const float gv = bf_round((ldsf(a) + ldsf(a + 512)) + (ldsf(a + 1024) + ldsf(a + 1536)));
                const float uv = bf_round((ldsf(a + 256) + ldsf(a + 768)) + (ldsf(a + 1280) + ldsf(a + 1792)));
                const float sg = bf_round(__fdividef(1.0f, 1.0f + __expf(-gv)));
                sts16(sb + OFF_Y + OP_H + (f >> 3) * 128 + b * 16 + (f & 7) * 2, sg * uv);
                fence_async();
            }
            bar_sync(3, 256);
            mbar_wait(BAR(B_WD), 0);
            if (tid == 0) STAMP(23);
            wg_fence();
            gemv_mmajor(e0, sd + (OFF_QA >> 4) + g * 512,       sd + ((OFF_Y + OP_H) >> 4), 0, 2, 1);
            gemv_mmajor(e1, sd + (OFF_QA >> 4) + g * 512 + 256, sd + ((OFF_Y + OP_H) >> 4), 0, 2, 1);
            wg_commit();
        }
        wg_wait<0>();
        if (q == 0) {
            uint4* p4 = sc->X4 + pr * 256 + r * 128 + g * 64 + w * 8 + rr;
            st_ll(p4,      (__float_as_uint(e0[0]) & ~1u) | tag, __float_as_uint(e0[1]), __float_as_uint(e0[2]), __float_as_uint(e0[3]));
            st_ll(p4 + 32, (__float_as_uint(e1[0]) & ~1u) | tag, __float_as_uint(e1[1]), __float_as_uint(e1[2]), __float_as_uint(e1[3]));
        }
    }
    STAMPW(5);

    if (warp < 2) {
        uint4 v[2];
        poll_ll_n<2>(v, sc->X4 + lane * 256 + fcc, 32 * 256, tag, T.bo_4);
        float v0 = __uint_as_float(v[0].x) + __uint_as_float(v[1].x), v1 = __uint_as_float(v[0].y) + __uint_as_float(v[1].y);
        float v2 = __uint_as_float(v[0].z) + __uint_as_float(v[1].z), v3 = __uint_as_float(v[0].w) + __uint_as_float(v[1].w);
        const bool b4 = lane & 16, b3 = lane & 8;
        float k0 = b4 ? v2 : v0, k1 = b4 ? v3 : v1, s0 = b4 ? v0 : v2, s1 = b4 ? v1 : v3;
        k0 += __shfl_xor_sync(0xffffffffu, s0, 16);
        k1 += __shfl_xor_sync(0xffffffffu, s1, 16);
        float k = b3 ? k1 : k0, s = b3 ? k0 : k1;
        k += __shfl_xor_sync(0xffffffffu, s, 8);
        k += __shfl_xor_sync(0xffffffffu, k, 4);
        k += __shfl_xor_sync(0xffffffffu, k, 2);
        k += __shfl_xor_sync(0xffffffffu, k, 1);
        if ((lane & 7) == 0) P.out[fb * 512 + fcol] = __float2bfloat16_rn(k + xres);
        if (tid == 0) STAMP(25);
    }
}

typedef CUresult (*PFN_encodeTiled)(CUtensorMap*, CUtensorMapDataType, cuuint32_t, void*, const cuuint64_t*, const cuuint64_t*,
                                    const cuuint32_t*, const cuuint32_t*, CUtensorMapInterleave, CUtensorMapSwizzle,
                                    CUtensorMapL2promotion, CUtensorMapFloatOOBfill);

void make_map(PFN_encodeTiled enc, CUtensorMap* m, const void* ptr, int rank, const cuuint64_t* dims, const cuuint64_t* strides,
              const cuuint32_t* box, CUtensorMapSwizzle sw) {
    cuuint32_t es[3] = {1, 1, 1};
    enc(m, CU_TENSOR_MAP_DATA_TYPE_BFLOAT16, rank, const_cast<void*>(ptr), dims, strides, box, es,
        CU_TENSOR_MAP_INTERLEAVE_NONE, sw, CU_TENSOR_MAP_L2_PROMOTION_NONE, CU_TENSOR_MAP_FLOAT_OOB_FILL_NONE);
}
void make_map2(PFN_encodeTiled enc, CUtensorMap* m, const void* ptr, uint64_t rows, uint64_t cols, uint32_t boxc, uint32_t boxr,
               CUtensorMapSwizzle sw = CU_TENSOR_MAP_SWIZZLE_128B) {
    cuuint64_t dims[2] = {cols, rows}; cuuint64_t strides[1] = {cols * 2}; cuuint32_t box[2] = {boxc, boxr};
    make_map(enc, m, ptr, 2, dims, strides, box, sw);
}

Tune g_tune = { 200, 100, 50, 400, 800, 0, 1500, 150, 0,
    { {G_WUK,0,0,4,1450,320}, {G_CKV0,0,0,4,2730,320}, {G_CKV1,0,0,4,4010,320}, {G_WO01,0,0,4,5290,160}, {G_WO23,0,0,4,5930,160},
      {G_WUV,0,0,4,9300,0}, {G_GU,0,0,4,-1,0}, {G_WD,0,0,4,-1,0}, {G_END,0,0,0,0,0} },
    { {G_WUV,1,0,4,6570,320}, {G_GU,1,0,4,7850,213}, {G_WD,1,0,4,8700,106}, {G_END,0,0,0,0,0} } };

}

extern "C" void kernel_launch(void* const* d_in, const int* in_sizes, int n_in, void* d_out, int out_size) {
    (void)in_sizes; (void)n_in; (void)out_size;
    static PFN_encodeTiled enc = nullptr;
    if (!enc) {
        void* fn = nullptr; cudaDriverEntryPointQueryResult qr;
        cudaGetDriverEntryPoint("cuTensorMapEncodeTiled", &fn, cudaEnableDefault, &qr);
        enc = (PFN_encodeTiled)fn;
        cudaFuncSetAttribute(mla_glu_kernel, cudaFuncAttributeMaxDynamicSharedMemorySize, SMEM_BYTES);
    }
    Params P;
    P.x = (const __nv_bfloat16*)d_in[0];
    P.out = (__nv_bfloat16*)d_out;
    static Scratch* scratch = nullptr;
    if (!scratch) cudaGetSymbolAddress((void**)&scratch, g_scratch);
    P.sc = scratch;
    make_map2(enc, &P.wq,  d_in[2], 512, 4096, 64, 128);
    make_map2(enc, &P.wuk, d_in[3], 512, 4096, 64, 32);
    {
        cuuint64_t dims[3] = {4096, 64, 8}; cuuint64_t strides[2] = {8192, 64 * 8192}; cuuint32_t box[3] = {64, 16, 2};
        make_map(enc, &P.wuv, d_in[4], 3, dims, strides, box, CU_TENSOR_MAP_SWIZZLE_128B);
    }
    make_map2(enc, &P.wo,  d_in[5], 4096, 512, 64, 32);
    make_map2(enc, &P.ckv, d_in[1], 8192, 512, 64, 32);
    make_map2(enc, &P.wg,  d_in[7], 512, 1376, 32, 128, CU_TENSOR_MAP_SWIZZLE_64B);
    make_map2(enc, &P.wu,  d_in[8], 512, 1376, 32, 128, CU_TENSOR_MAP_SWIZZLE_64B);
    make_map2(enc, &P.wd,  d_in[9], 1376, 512, 64, 32);
    P.tune = g_tune;
    mla_glu_kernel<<<NCTA, NTHREADS, SMEM_BYTES, cudaStreamPerThread>>>(P);
}
```

```cpp
#include <cuda_runtime.h>
#include <cuda_bf16.h>
#include <cuda.h>
#include <stdint.h>

namespace {

constexpr int NCTA     = 128;
constexpr int NTHREADS = 352;
constexpr int SPIN_LIMIT = 1 << 22;
constexpr int NGLU     = 43;

constexpr uint32_t OFF_RA  = 0;
constexpr uint32_t OFF_RB  = 65536;
constexpr uint32_t OFF_R0  = 131072;
constexpr uint32_t OFF_GU  = OFF_RB + 32768;
constexpr uint32_t OFF_R1  = 163840;
constexpr uint32_t OFF_QA  = 196608;
constexpr uint32_t OFF_XN  = 212992;
constexpr uint32_t OFF_Y   = OFF_XN + 2048;
constexpr uint32_t OP_Q = 0, OP_CL = 32, OP_CX = 64, OP_H = 96;
constexpr uint32_t OFF_P0  = OFF_Y + 2048 + 128;
constexpr uint32_t OFF_P1  = OFF_P0 + 2048;
constexpr uint32_t OFF_PA  = OFF_P1 + 2048;
constexpr uint32_t OFF_PG  = OFF_PA + 2048;
constexpr uint32_t OFF_ST  = OFF_PG + 2048;
constexpr uint32_t ST_WMAX = 0;
constexpr uint32_t ST_LSUM = 512;
constexpr uint32_t ST_M0   = 1024;
constexpr uint32_t ST_M1   = 1088;
constexpr uint32_t ST_STG  = 1280;
constexpr uint32_t OFF_BAR = OFF_ST + 1792;
constexpr uint32_t OFF_T0  = OFF_BAR + 256;
constexpr uint32_t OFF_ONES = OFF_BAR + 512;
constexpr uint32_t OFF_STAMP = OFF_ONES + 2048;
constexpr uint32_t SMEM_USED = OFF_STAMP + 1024;
constexpr uint32_t SMEM_BYTES = SMEM_USED + 1024;
static_assert(SMEM_BYTES <= 232448, "smem");
static_assert((OFF_P0 % 128) == 0 && (OFF_PA % 16) == 0 && (OFF_ST % 16) == 0 && (OFF_BAR % 8) == 0, "align");

enum { B_WQ = 0  , B_WUK = 4, B_CKV = 5  , B_G1 = 9, B_WUV = 10, B_WO = 11  , B_WD = 15,
       B_XA = 16, B_XG = 17, B_XD = 18,
       B_INIT2 = 19, B_EVX2 = 13, B_EVST = 14,
       B_FREEA = 20, B_FREE1 = 21, B_FREEB = 22, B_FREEQ = 23, B_EVX1 = 24, B_T0 = 25, NBARS = 26 };
static_assert(NBARS * 8 <= 256, "bars");

struct Ent { signed char grp, kind, s0, s1; short t, dt; };
enum { G_WUK = 0, G_CKV0, G_CKV1, G_WO01, G_WO23, G_WUV, G_GU, G_WD, G_END };
struct Tune {
    int   bo_1, bo_2, bo_4;
    int   dl_1, dl_2;
    int   mode;
    int   t_init2;
    int   dt_init2;
    int   stag;
    int   t_4;
    int   t_1, t_2;
    int   gpos;
    int   remap;
    int   o_wo0, o_wo1, o_wuv, o_gu;
    int   f_wo0, f_wo1, f_wuv, f_gu;
    Ent   la[14], lb[14];
};

struct Scratch {
    uint4 X2[128 * 64 * 16];
    uint4 X4[64 * 256];
    uint4 X1[2 * 32 * 64];
    uint4 XS[32 * 64 * 2];
    unsigned epoch[NCTA * 8];
};

struct Params {
    const __nv_bfloat16* x;
    Scratch* sc;
    __nv_bfloat16* out;
    Tune tune;
    alignas(64) CUtensorMap wq, wuk, ckv, wg, wu, wuv, wo, wd;
};

__device__ Scratch g_scratch;
#define CK_(i) do {} while (0)
#define CKB_(i) do {} while (0)
#define STAMP(i) do {} while (0)
#define STAMPC(i) do {} while (0)
#define STAMPW(i) do {} while (0)
__device__ __forceinline__ uint32_t smem_u32(const void* p) { return (uint32_t)__cvta_generic_to_shared(p); }
__device__ __forceinline__ unsigned long long gtime() {
    unsigned long long t; asm volatile("mov.u64 %0, %%globaltimer;" : "=l"(t)); return t;
}
__device__ __forceinline__ void mbar_init(uint32_t bar, uint32_t cnt) {
    asm volatile("mbarrier.init.shared::cta.b64 [%0], %1;" :: "r"(bar), "r"(cnt) : "memory");
}
__device__ __forceinline__ void mbar_expect_tx(uint32_t bar, uint32_t bytes) {
    asm volatile("mbarrier.arrive.expect_tx.shared::cta.b64 _, [%0], %1;" :: "r"(bar), "r"(bytes) : "memory");
}
__device__ __forceinline__ void mbar_arrive(uint32_t bar) {
    asm volatile("mbarrier.arrive.shared::cta.b64 _, [%0];" :: "r"(bar) : "memory");
}
__device__ __forceinline__ void mbar_wait(uint32_t bar, uint32_t parity) {
    uint32_t done; int it = 0;
    do {
        asm volatile("{\n.reg .pred p;\nmbarrier.try_wait.parity.shared::cta.b64 p, [%1], %2;\nselp.u32 %0, 1, 0, p;\n}"
                     : "=r"(done) : "r"(bar), "r"(parity) : "memory");
    } while (!done && ++it < SPIN_LIMIT);
    if (!done) __trap();
}
__device__ __forceinline__ void tma2d(uint32_t dst, const CUtensorMap* m, int c0, int c1, uint32_t bar) {
    asm volatile("cp.async.bulk.tensor.2d.shared::cluster.global.mbarrier::complete_tx::bytes [%0], [%1, {%3,%4}], [%2];"
                 :: "r"(dst), "l"(m), "r"(bar), "r"(c0), "r"(c1) : "memory");
}
__device__ __forceinline__ void tma3d(uint32_t dst, const CUtensorMap* m, int c0, int c1, int c2, uint32_t bar) {
    asm volatile("cp.async.bulk.tensor.3d.shared::cluster.global.mbarrier::complete_tx::bytes [%0], [%1, {%3,%4,%5}], [%2];"
                 :: "r"(dst), "l"(m), "r"(bar), "r"(c0), "r"(c1), "r"(c2) : "memory");
}
__device__ __forceinline__ void tma2d_pf(const CUtensorMap* m, int c0, int c1) {
    asm volatile("cp.async.bulk.prefetch.tensor.2d.L2.global.tile [%0, {%1,%2}];" :: "l"(m), "r"(c0), "r"(c1) : "memory");
}
__device__ __forceinline__ void tma3d_pf(const CUtensorMap* m, int c0, int c1, int c2) {
    asm volatile("cp.async.bulk.prefetch.tensor.3d.L2.global.tile [%0, {%1,%2,%3}];" :: "l"(m), "r"(c0), "r"(c1), "r"(c2) : "memory");
}
__device__ __forceinline__ void bulk_pf(const void* src, uint32_t bytes) {
    asm volatile("cp.async.bulk.prefetch.L2.global [%0], %1;" :: "l"(src), "r"(bytes) : "memory");
}
__device__ __forceinline__ void pf_map(const CUtensorMap* m) {
    asm volatile("prefetch.tensormap [%0];" :: "l"(m) : "memory");
}
__device__ __forceinline__ void bar_sync(int id, int n) { asm volatile("bar.sync %0, %1;" :: "r"(id), "r"(n) : "memory"); }
__device__ __forceinline__ void bar_arrive(int id, int n) { asm volatile("bar.arrive %0, %1;" :: "r"(id), "r"(n) : "memory"); }
__device__ __forceinline__ void fence_async() { asm volatile("fence.proxy.async.shared::cta;" ::: "memory"); }

__device__ __forceinline__ void st_ll(uint4* p, uint32_t a, uint32_t b, uint32_t c, uint32_t d) {
    asm volatile("st.relaxed.gpu.global.v4.u32 [%0], {%1,%2,%3,%4};" :: "l"(p), "r"(a), "r"(b), "r"(c), "r"(d) : "memory");
}
__device__ __forceinline__ uint4 ld_ll(const uint4* p) {
    uint4 v;
    asm volatile("ld.relaxed.gpu.global.v4.u32 {%0,%1,%2,%3}, [%4];" : "=r"(v.x), "=r"(v.y), "=r"(v.z), "=r"(v.w) : "l"(p) : "memory");
    return v;
}
__device__ __forceinline__ void spin_clk(int n) {
    uint32_t c0, c; asm volatile("mov.u32 %0, %%clock;" : "=r"(c0));
    do { asm volatile("mov.u32 %0, %%clock;" : "=r"(c)); } while ((int)(c - c0) < n);
}
__device__ __forceinline__ uint4 poll_ll(const uint4* p, uint32_t tag, int backoff) {
    uint4 v = ld_ll(p); int it = 0;
    while (((v.x ^ tag) & 1u) && ++it < SPIN_LIMIT) { spin_clk(backoff); v = ld_ll(p); }
    if ((v.x ^ tag) & 1u) __trap();
    v.x &= ~1u;
    return v;
}
template <int N>
__device__ __forceinline__ void poll_ll_n(uint4 (&v)[N], const uint4* p, int stride, uint32_t tag, int backoff) {
    uint32_t pend = 0; int it = 0;
#pragma unroll
    for (int i = 0; i < N; i++) v[i] = ld_ll(p + i * stride);
#pragma unroll
    for (int i = 0; i < N; i++) if ((v[i].x ^ tag) & 1u) pend |= 1u << i;
    while (pend && ++it < SPIN_LIMIT) {
        spin_clk(backoff);
#pragma unroll
        for (int i = 0; i < N; i++) if (pend & (1u << i)) v[i] = ld_ll(p + i * stride);
#pragma unroll
        for (int i = 0; i < N; i++) if (!((v[i].x ^ tag) & 1u)) pend &= ~(1u << i);
    }
    if (pend) __trap();
#pragma unroll
    for (int i = 0; i < N; i++) v[i].x &= ~1u;
}

__device__ __forceinline__ uint64_t mk_desc(uint32_t sa16, uint32_t lbo, uint32_t sbo, uint32_t swz) {
    const uint32_t lo = sa16 + ((lbo >> 4) << 16);
    const uint32_t hi = (sbo >> 4) | (swz << 30);
    return ((uint64_t)hi << 32) | lo;
}
__device__ __forceinline__ void wg_fence()  { asm volatile("wgmma.fence.sync.aligned;" ::: "memory"); }
__device__ __forceinline__ void wg_commit() { asm volatile("wgmma.commit_group.sync.aligned;" ::: "memory"); }
template <int N> __device__ __forceinline__ void wg_wait() { asm volatile("wgmma.wait_group.sync.aligned %0;" :: "n"(N) : "memory"); }

template <int TA, int TB>
__device__ __forceinline__ void mma_n8(float (&d)[4], uint64_t da, uint64_t db, int acc) {
    asm volatile("{\n.reg .pred p;\nsetp.ne.b32 p, %6, 0;\n"
                 "wgmma.mma_async.sync.aligned.m64n8k16.f32.bf16.bf16 {%0,%1,%2,%3}, %4, %5, p, 1, 1, %7, %8;\n}\n"
                 : "+f"(d[0]), "+f"(d[1]), "+f"(d[2]), "+f"(d[3])
                 : "l"(da), "l"(db), "r"(acc), "n"(TA), "n"(TB));
}
template <int TA, int TB>
__device__ __forceinline__ void mma_n16(float (&d)[8], uint64_t da, uint64_t db, int acc) {
    asm volatile("{\n.reg .pred p;\nsetp.ne.b32 p, %10, 0;\n"
                 "wgmma.mma_async.sync.aligned.m64n16k16.f32.bf16.bf16 {%0,%1,%2,%3,%4,%5,%6,%7}, %8, %9, p, 1, 1, %11, %12;\n}\n"
                 : "+f"(d[0]), "+f"(d[1]), "+f"(d[2]), "+f"(d[3]), "+f"(d[4]), "+f"(d[5]), "+f"(d[6]), "+f"(d[7])
                 : "l"(da), "l"(db), "r"(acc), "n"(TA), "n"(TB));
}

__device__ __forceinline__ float bf_round(float v) { return __bfloat162float(__float2bfloat16_rn(v)); }
__device__ __forceinline__ uint32_t pack_bf(float lo, float hi) {
    uint32_t r; asm("cvt.rn.bf16x2.f32 %0, %1, %2;" : "=r"(r) : "f"(hi), "f"(lo)); return r;
}
__device__ __forceinline__ float bf_lo(uint32_t w) { return __uint_as_float(w << 16); }
__device__ __forceinline__ float bf_hi(uint32_t w) { return __uint_as_float(w & 0xFFFF0000u); }
__device__ __forceinline__ float ex2(float v) { float r; asm("ex2.approx.ftz.f32 %0, %1;" : "=f"(r) : "f"(v)); return r; }
__device__ __forceinline__ void sts16(uint32_t a, float v) {
    unsigned short s = __bfloat16_as_ushort(__float2bfloat16_rn(v));
    asm volatile("st.shared.u16 [%0], %1;" :: "r"(a), "h"(s) : "memory");
}
__device__ __forceinline__ void sts32(uint32_t a, uint32_t v) { asm volatile("st.shared.u32 [%0], %1;" :: "r"(a), "r"(v) : "memory"); }
__device__ __forceinline__ void stsf(uint32_t a, float v) { asm volatile("st.shared.f32 [%0], %1;" :: "r"(a), "f"(v) : "memory"); }
__device__ __forceinline__ float ldsf(uint32_t a) { float v; asm volatile("ld.shared.f32 %0, [%1];" : "=f"(v) : "r"(a) : "memory"); return v; }
__device__ __forceinline__ float4 ldsf4(uint32_t a) {
    float4 v; asm volatile("ld.shared.v4.f32 {%0,%1,%2,%3}, [%4];" : "=f"(v.x), "=f"(v.y), "=f"(v.z), "=f"(v.w) : "r"(a) : "memory"); return v;
}
__device__ __forceinline__ void wait_until(unsigned long long t) { while (gtime() < t) {} }

__device__ __forceinline__ uint32_t mapa(uint32_t addr, uint32_t rank) {
    uint32_t r; asm("mapa.shared::cluster.u32 %0, %1, %2;" : "=r"(r) : "r"(addr), "r"(rank)); return r;
}
__device__ __forceinline__ void st_async4(uint32_t dst, const float (&v)[4], uint32_t bar) {
    asm volatile("st.async.weak.shared::cluster.mbarrier::complete_tx::bytes.v4.f32 [%0], {%1,%2,%3,%4}, [%5];"
                 :: "r"(dst), "f"(v[0]), "f"(v[1]), "f"(v[2]), "f"(v[3]), "r"(bar) : "memory");
}
__device__ __forceinline__ void mbar_wait_cluster(uint32_t bar, uint32_t parity) {
    uint32_t done; int it = 0;
    do {
        asm volatile("{\n.reg .pred p;\nmbarrier.try_wait.parity.acquire.cluster.shared::cta.b64 p, [%1], %2;\nselp.u32 %0, 1, 0, p;\n}"
                     : "=r"(done) : "r"(bar), "r"(parity) : "memory");
    } while (!done && ++it < SPIN_LIMIT);
    if (!done) __trap();
}

__device__ __forceinline__ void gemv_mmajor(float (&acc)[4], uint32_t a_base, uint32_t b_base, int ks0, int ks1, int first_acc) {
#pragma unroll
    for (int ks = 0; ks < 8; ks++) {
        if (ks >= ks0 && ks < ks1)
            mma_n8<1, 0>(acc, mk_desc(a_base + ks * 128, 1024, 1024, 1), mk_desc(b_base + ks * 16, 128, 128, 0), (ks > ks0) | first_acc);
    }
}

__global__ void __cluster_dims__(2, 1, 1) __launch_bounds__(NTHREADS, 1)
mla_glu_kernel(const __grid_constant__ Params P)
{
    extern __shared__ uint8_t smem_raw[];
    const int tid = threadIdx.x, lane = tid & 31;
    const int bid = blockIdx.x;
    const unsigned long long t0 = gtime();
    uint4 xa, xb; float x0 = 0.f;
    if ((tid & 127) < 32 && tid < 256) {
        const __nv_bfloat16* xr = P.x + (tid >> 7) * 512;
        const uint4* xp = reinterpret_cast<const uint4*>(xr + lane * 16);
        xa = xp[0]; xb = xp[1];
        x0 = __bfloat162float(xr[0]);
    }
    const uint32_t sb = (smem_u32(smem_raw) + 1023u) & ~1023u;
    const uint32_t bars = sb + OFF_BAR;
    auto BAR = [&](int i) { return bars + 8u * i; };
    const int pr = bid >> 1, r = bid & 1;
    int h = bid >> 2, j = bid & 3;
    if (P.tune.remap) {
        int hh, half;
        if (pr < 4)       { hh = 30 + (pr >> 1); half = pr & 1; }
        else if (pr < 36) { const int i = pr - 4; hh = ((i >> 4) << 3) + (i & 7); half = (i >> 3) & 1; }
        else              { const int i = pr - 36, row = i / 7; hh = 16 + (row >> 1) * 7 + (i - row * 7); half = row & 1; }
        h = hh; j = 2 * half + r;
    }
    if (tid == 288) {
#pragma unroll
        for (int i = 0; i < 4; i++) mbar_init(BAR(B_WQ + i), 1);
        asm volatile("fence.mbarrier_init.release.cluster;" ::: "memory");
#pragma unroll
        for (int i = 0; i < 4; i++) {
            mbar_expect_tx(BAR(B_WQ + i), 16384);
            tma2d(sb + OFF_RA + i * 16384, &P.wq, h * 128 + r * 64, i * 128, BAR(B_WQ + i));
        }
        STAMP(29);
#pragma unroll
        for (int i = 4; i < NBARS; i++) mbar_init(BAR(i), (i == B_EVST || i == B_EVX1) ? 8 : ((i >= B_FREEA && i <= B_FREEQ) || i == B_EVX2) ? 2 : 1);
        mbar_expect_tx(BAR(B_T0), 8); mbar_expect_tx(BAR(B_XA), 2048); mbar_expect_tx(BAR(B_XG), 2048); mbar_expect_tx(BAR(B_XD), 2048);
        asm volatile("fence.mbarrier_init.release.cluster;" ::: "memory");
        fence_async();
    }
    __syncwarp();
    asm volatile("barrier.cluster.arrive.relaxed.aligned;" ::: "memory");
    const int warp = __shfl_sync(0xffffffffu, tid >> 5, 0);
    const uint32_t sd = (sb & 0x3FFFFu) >> 4;
    const bool glu = pr < NGLU;
    Scratch* const sc = P.sc;

    if (warp >= 8) {
      if (warp == 9 || warp == 8) {
        bar_arrive(0, NTHREADS);
        asm volatile("barrier.cluster.wait.acquire.aligned;" ::: "memory");
        if (lane == 0) {
            unsigned long long tp;
            if (warp == 8 && r == 0) {
#pragma unroll
                for (int i = 0; i < 2; i++)
                    asm volatile("st.async.weak.shared::cluster.mbarrier::complete_tx::bytes.b64 [%0], %1, [%2];"
                                 :: "r"(mapa(sb + OFF_T0, i)), "l"(t0), "r"(mapa(BAR(B_T0), i)) : "memory");
            }
            mbar_wait_cluster(BAR(B_T0), 0);
            asm volatile("ld.shared.u64 %0, [%1];" : "=l"(tp) : "r"(sb + OFF_T0) : "memory");
            if (P.tune.mode & 64) tp = t0;
            if (warp == 9) { pf_map(&P.wuk); pf_map(&P.ckv); pf_map(&P.wg); pf_map(&P.wu); pf_map(&P.wuv); pf_map(&P.wo); pf_map(&P.wd); }
            const Ent* list = (warp == 9) ? P.tune.la : P.tune.lb;
            const unsigned long long tb = tp + (((pr * 11) & 31) * P.tune.stag >> 5);
#pragma unroll 1
            for (int e = 0; e < 14; e++) {
                const Ent E = list[e];
                if (E.grp >= G_END) break;
                if (E.grp >= G_GU && !glu) continue;
                const bool pf = E.kind != 0;
                unsigned long long tn;
                if (E.t == -2) mbar_wait(BAR(B_EVX2), 0);
                if (E.t == -3) mbar_wait(BAR(B_EVST), 0);
                if (E.t == -4) mbar_wait(BAR(B_EVX1), 0);
                if (E.t >= 0) tn = tb + E.t; else tn = gtime();
                const int dt = E.dt;
                bool first = true;
                auto step = [&]() { if (first || dt) wait_until(tn); first = false; tn += dt; };
                const int s0 = E.s0, s1 = E.s1;
                switch (E.grp) {
                case G_WUK:
                    if (!pf && s0 == 0) mbar_expect_tx(BAR(B_WUK), 32768);
#pragma unroll 1
                    for (int i = s0; i < s1; i++) {
                        step();
                        if (pf) { tma2d_pf(&P.wuk, h * 128, j * 128 + i * 32); tma2d_pf(&P.wuk, h * 128 + 64, j * 128 + i * 32); }
                        else {
                            tma2d(sb + OFF_R1 + i * 4096,         &P.wuk, h * 128,      j * 128 + i * 32, BAR(B_WUK));
                            tma2d(sb + OFF_R1 + 16384 + i * 4096, &P.wuk, h * 128 + 64, j * 128 + i * 32, BAR(B_WUK));
                        }
                    }
                    break;
                case G_CKV0: case G_CKV1: {
                    const int t = E.grp - G_CKV0;
                    if (!pf && t) mbar_wait(BAR(B_FREEA), 0);
#pragma unroll 1
                    for (int k = s0; k < s1; k++) {
                        const int ps = k >> 1, rh = k & 1;
                        step();
                        if (pf) {
#pragma unroll
                            for (int u = 0; u < 2; u++) tma2d_pf(&P.ckv, (ps * 4 + r * 2 + u) * 64, pr * 128 + t * 64 + rh * 32);
                        } else {
                            if (!rh) mbar_expect_tx(BAR(B_CKV + t * 2 + ps), 32768);
#pragma unroll
                            for (int u = 0; u < 4; u++)
                                tma2d(sb + (t ? OFF_RA : OFF_RB) + (ps * 4 + u) * 8192 + rh * 4096, &P.ckv, (ps * 4 + u) * 64, pr * 128 + t * 64 + rh * 32,
                                      BAR(B_CKV + t * 2 + ps));
                        }
                    }
                    break; }
                case G_WO01: case G_WO23: {
                    const int t = E.grp - G_WO01;
                    const int fo = t ? P.tune.f_wo1 : P.tune.f_wo0;
                    const uint32_t dst = sb + (t ? P.tune.o_wo1 : P.tune.o_wo0);
                    if (!pf) { if (fo >= 0) mbar_wait(BAR(fo), 0); if (s0 == 0) mbar_expect_tx(BAR(B_WO + t), 32768); }
#pragma unroll 1
                    for (int kq = s0; kq < s1; kq++) {
                        step();
                        if (pf) tma2d_pf(&P.wo, r * 256 + t * 128 + (j >> 1) * 64, h * 128 + kq * 32);
                        else {
                            tma2d(dst + kq * 4096,         &P.wo, r * 256 + t * 128,      h * 128 + kq * 32, BAR(B_WO + t));
                            tma2d(dst + 16384 + kq * 4096, &P.wo, r * 256 + t * 128 + 64, h * 128 + kq * 32, BAR(B_WO + t));
                        }
                    }
                    break; }
                case G_WUV:
                    if (!pf) { if (P.tune.f_wuv >= 0) mbar_wait(BAR(P.tune.f_wuv), 0); if (s0 == 0) mbar_expect_tx(BAR(B_WUV), 32768); }
#pragma unroll 1
                    for (int i = s0; i < s1; i++) {
                        step();
                        if (pf) { tma3d_pf(&P.wuv, h * 128, j * 16, i * 2); tma3d_pf(&P.wuv, h * 128 + 64, j * 16, i * 2); }
                        else {
                            tma3d(sb + P.tune.o_wuv + i * 4096,         &P.wuv, h * 128,      j * 16, i * 2, BAR(B_WUV));
                            tma3d(sb + P.tune.o_wuv + 16384 + i * 4096, &P.wuv, h * 128 + 64, j * 16, i * 2, BAR(B_WUV));
                        }
                    }
                    break;
                case G_GU:
                    if (!pf) { if (P.tune.f_gu >= 0) mbar_wait(BAR(P.tune.f_gu), 0); if (s0 == 0) mbar_expect_tx(BAR(B_G1), 32768); }
#pragma unroll 1
                    for (int i = s0; i < s1; i++) {
                        step();
                        if (pf) tma2d_pf((i & 1) ? &P.wu : &P.wg, pr * 32, (2 * r + (i >> 1)) * 128);
                        else tma2d(sb + P.tune.o_gu + i * 8192, (i & 1) ? &P.wu : &P.wg, pr * 32, (2 * r + (i >> 1)) * 128, BAR(B_G1));
                    }
                    break;
                default:
                    if (!pf) { mbar_wait(BAR(B_FREEQ), 0); if (s0 == 0) mbar_expect_tx(BAR(B_WD), 16384); }
#pragma unroll 1
                    for (int i = s0; i < s1; i++) {
                        step();
                        if (pf) tma2d_pf(&P.wd, r * 256 + i * 64, pr * 32);
                        else tma2d(sb + OFF_QA + i * 4096, &P.wd, r * 256 + i * 64, pr * 32, BAR(B_WD));
                    }
                    break;
                }
                STAMP(128 + (warp == 8) * 16 + e);
            }
            STAMP(35 - (warp == 8));
        }
      } else if (warp == 10) {
        const uint32_t ntag = sc->epoch[bid * 8] & 1u;
        if (ntag < 2 && lane == 0) STAMP(26);
        st_ll(sc->X1 + ((lane >> 4) * 32 + h) * 64 + 16 * j + (lane & 15), ntag, 0, 0, 0);
        st_ll(sc->XS + ((16 * r + (lane >> 1)) * 64 + pr) * 2 + (lane & 1), ntag, 0, 0, 0);
#pragma unroll
        for (int i = 0; i < 4; i++) st_ll(sc->X4 + pr * 256 + r * 128 + i * 32 + lane, ntag, 0, 0, 0);
        bar_sync(0, NTHREADS);
        uint4* px2 = sc->X2 + ((size_t)((16 * r) * 4 + (lane >> 4)) * 64 + pr) * 16 + (lane & 15);
        if (!(P.tune.mode & 1)) {
            unsigned long long tn = t0 + P.tune.t_init2;
#pragma unroll 1
            for (int i = 0; i < 32; i++) {
                wait_until(tn); tn += P.tune.dt_init2;
                st_ll(px2 + i * (2 * 64 * 16), ntag, 0, 0, 0);
            }
        }
        __syncwarp();
        asm volatile("fence.acq_rel.cta;" ::: "memory");
        if (lane == 0) { mbar_arrive(BAR(B_INIT2)); STAMP(27); }
      }
      return;
    }

    const int g  = warp >> 2;
    const int w  = warp & 3;
    const int tg = tid & 127;
    const int rr = lane >> 2, q = lane & 3;
    const Tune& T = P.tune;

    if (tid == 0) STAMPC(36);
    const unsigned ep = sc->epoch[bid * 8];
    const int fcc = 2 * bid + (warp & 1);
    const int fcol = 256 * (fcc >> 7) + 64 * ((fcc >> 5) & 3) + 16 * ((fcc >> 3) & 3) + (fcc & 7) + 8 * (lane >> 4);
    const int fb = (lane >> 3) & 1;
    float xres = 0.f;
    if (w == 0) {
        const uint32_t xw[8] = { xa.x, xa.y, xa.z, xa.w, xb.x, xb.y, xb.z, xb.w };
        float xv[16];
#pragma unroll
        for (int i = 0; i < 8; i++) { xv[2 * i] = bf_lo(xw[i]); xv[2 * i + 1] = bf_hi(xw[i]); }
        float s = 0.f, s2 = 0.f;
#pragma unroll
        for (int i = 0; i < 16; i++) { const float d = xv[i] - x0; s += d; s2 = fmaf(d, d, s2); }
        if (tid == 0 && s != 12345.f) STAMPC(28);
#pragma unroll
        for (int o = 16; o; o >>= 1) { s += __shfl_xor_sync(0xffffffffu, s, o); s2 += __shfl_xor_sync(0xffffffffu, s2, o); }
        const float md = s * (1.0f / 512.0f);
        const float var = fmaxf(fmaf(-md, md, s2 * (1.0f / 512.0f)), 0.f);
        const float mb = bf_round(x0 + md);
        const float rs = __frcp_rn(bf_round(__fsqrt_rn(bf_round(bf_round(var) + 1e-5f))));
        uint32_t o[8];
#pragma unroll
        for (int i = 0; i < 8; i++) o[i] = pack_bf(bf_round(xv[2 * i] - mb) * rs, bf_round(xv[2 * i + 1] - mb) * rs);
        const uint32_t a = sb + OFF_XN + (lane >> 3) * 32 + (lane & 7) * 256 + g * 16;
        asm volatile("st.shared.v4.u32 [%0], {%1,%2,%3,%4};" :: "r"(a), "r"(o[0]), "r"(o[1]), "r"(o[2]), "r"(o[3]) : "memory");
        asm volatile("st.shared.v4.u32 [%0], {%1,%2,%3,%4};" :: "r"(a + 128), "r"(o[4]), "r"(o[5]), "r"(o[6]), "r"(o[7]) : "memory");
        if (tid == 0) STAMPC(30);
        fence_async();
    }
    if (g == 1) {
        asm volatile("st.shared.v4.u32 [%0], {%1,%1,%1,%1};" :: "r"(sb + OFF_ONES + tg * 16), "r"(0x3F803F80u) : "memory");
        fence_async();
    }
    if (warp < 2) xres = __bfloat162float(P.x[fb * 512 + fcol]);
    const uint32_t tag = (ep + 1u) & 1u;
    const uint32_t ch16 = (w * 8 + rr) * 16;
    const uint32_t own_sb = mapa(sb, r), peer_sb = mapa(sb, r ^ 1);

    bar_sync(0, NTHREADS);
    if (tid == 0) sc->epoch[bid * 8] = ep + 1u;
    if (tid == 0) { STAMPC(0); }
    CK_(0);

    auto gather2 = [&](uint32_t buf, uint32_t op) {
        const int d = tid >> 1, b = tid & 1;
        const uint32_t a = buf + (d >> 6) * 1024 + (((d >> 4) & 3) * 8 + (d & 7)) * 16 + (((d >> 3) & 1) * 2 + b) * 4;
        sts16(op + (d >> 3) * 128 + b * 16 + (d & 7) * 2, ldsf(a) + ldsf(a + 512));
        fence_async();
    };

    float acc[4];
    auto phaseG = [&]() {
        if (glu) {
            float ga[4];
            mbar_wait(BAR(B_G1), 0);
            wg_fence();
#pragma unroll
            for (int ks = 0; ks < 8; ks++)
                mma_n8<1, 0>(ga, mk_desc(sd + ((T.o_gu + ks * 1024) >> 4) + g * 1024, 8192, 512, 2),
                             mk_desc(sd + ((OFF_XN + ks * 256) >> 4) + (2 * r + g) * 2, 128, 128, 0), ks > 0);
            wg_commit(); wg_wait<0>();
            if (q == 0) {
                const uint32_t o2 = OFF_PG + r * 1024 + g * 512 + ch16;
                st_async4(own_sb + o2, ga, own_sb + OFF_BAR + 8 * B_XG);
                st_async4(peer_sb + o2, ga, peer_sb + OFF_BAR + 8 * B_XG);
            }
        }
    };
    auto phaseH = [&]() {
        if (glu && tid < 64) {
            mbar_wait_cluster(BAR(B_XG), 0);
            const int f = tid >> 1, b = tid & 1;
            const uint32_t a = sb + OFF_PG + ((f >> 4) * 8 + (f & 7)) * 16 + (((f >> 3) & 1) * 2 + b) * 4;
            const float gv = bf_round((ldsf(a) + ldsf(a + 512)) + (ldsf(a + 1024) + ldsf(a + 1536)));
            const float uv = bf_round((ldsf(a + 256) + ldsf(a + 768)) + (ldsf(a + 1280) + ldsf(a + 1792)));
            const float sg = bf_round(__fdividef(1.0f, 1.0f + __expf(-gv)));
            sts16(sb + OFF_Y + OP_H + (f >> 3) * 128 + b * 16 + (f & 7) * 2, sg * uv);
            fence_async();
        }
    };
    mbar_wait(BAR(B_WQ + 2 * g), 0);
    wg_fence();
    gemv_mmajor(acc, sd + ((OFF_RA + 2 * g * 16384) >> 4), sd + ((OFF_XN + 2 * g * 32) >> 4), 0, 8, 0);
    wg_commit();
    mbar_wait(BAR(B_WQ + 2 * g + 1), 0);
    if (tid == 0) STAMPC(1);
    wg_fence();
    gemv_mmajor(acc, sd + ((OFF_RA + (2 * g + 1) * 16384) >> 4), sd + ((OFF_XN + (2 * g + 1) * 32) >> 4), 0, 8, 1);
    wg_commit();
    asm volatile("barrier.cluster.wait.acquire.aligned;" ::: "memory");
    wg_wait<0>();
    if (tg == 0) mbar_arrive(BAR(B_FREEA));
    if (q == 0) {
        const uint32_t o = OFF_PA + r * 1024 + g * 512 + ch16;
        st_async4(own_sb + o, acc, own_sb + OFF_BAR + 8 * B_XA);
        st_async4(peer_sb + o, acc, peer_sb + OFF_BAR + 8 * B_XA);
    }
    if (tid == 0) STAMPC(6);
    mbar_wait_cluster(BAR(B_XA), 0);
    if (tid == 0) STAMPC(7);
    gather2(sb + OFF_PA, sb + OFF_Y + OP_Q);
    bar_sync(3, 256);
    if (tid == 0) STAMPC(2);

    mbar_wait(BAR(B_WUK), 0);
    if (tid == 0) STAMPC(3);
    wg_fence();
#pragma unroll
    for (int ks = 0; ks < 8; ks++)
        mma_n8<0, 0>(acc, mk_desc(sd + ((OFF_R1 + (ks >> 2) * 16384 + (ks & 3) * 32) >> 4) + g * 512, 16, 1024, 1),
                     mk_desc(sd + ((OFF_Y + OP_Q + ks * 256) >> 4), 128, 128, 0), ks > 0);
    wg_commit(); wg_wait<0>();
    if (tg == 0) mbar_arrive(BAR(B_FREE1));
    {
        const float qs = 0.08838834764831845f * 1.4426950408889634f;
        const uint32_t stg = sb + OFF_ST + ST_STG + warp * 64;
        if (q == 0) {
            sts16(stg + rr * 2,           acc[0] * qs);
            sts16(stg + 32 + rr * 2,      acc[1] * qs);
            sts16(stg + 16 + rr * 2,      acc[2] * qs);
            sts16(stg + 32 + 16 + rr * 2, acc[3] * qs);
        }
        __syncwarp();
        if (lane < 4) {
            uint4 v;
            asm volatile("ld.shared.v4.u32 {%0,%1,%2,%3}, [%4];" : "=r"(v.x), "=r"(v.y), "=r"(v.z), "=r"(v.w) : "r"(stg + lane * 16) : "memory");
            st_ll(sc->X1 + ((lane >> 1) * 32 + h) * 64 + 16 * j + 8 * g + 2 * w + (lane & 1), (v.x & ~1u) | tag, v.y, v.z, v.w);
        }
    }
    STAMPW(0);
    {
        const uint4* src = sc->X1 + ((pr >> 5) * 32 + 16 * r) * 64;
        uint4 v[4];
        spin_clk(T.dl_1);
        if (T.t_1 > 0) wait_until(t0 + T.t_1);
        poll_ll_n<4>(v, src + tid, 256, tag, T.bo_1);
        __syncwarp();
        if (lane == 0) mbar_arrive(BAR(B_EVX1));
        STAMPW(1);
        CK_(1);
#pragma unroll
        for (int i = 0; i < 4; i++) {
            const int idx = i * 256 + tid, n = idx >> 6, kc = idx & 63;
            const uint32_t a = sb + OFF_QA + (kc >> 3) * 2048 + n * 128 + (((kc & 7) ^ (n & 7)) << 4);
            asm volatile("st.shared.v4.u32 [%0], {%1,%2,%3,%4};" :: "r"(a), "r"(v[i].x), "r"(v[i].y), "r"(v[i].z), "r"(v[i].w) : "memory");
        }
        fence_async();
    }
    bar_sync(3, 256);
    if (tid == 0) STAMPC(5);
    CKB_(2);

    float o[4][8];
    float pr8[8], s[8], m[4];
    const uint32_t st = sb + OFF_ST;
    const uint32_t wm = st + ST_WMAX + g * 256;
    auto scores = [&]() {
        const uint32_t tile = sd + ((g ? OFF_RA : OFF_RB) >> 4);
#pragma unroll
        for (int u = 0; u < 8; u++) {
            if ((u & 3) == 0) mbar_wait(BAR(B_CKV + g * 2 + (u >> 2)), 0);
            wg_fence();
#pragma unroll
            for (int ks = 0; ks < 4; ks++)
                mma_n16<0, 0>(s, mk_desc(tile + ((u * 8192 + ks * 32) >> 4), 16, 1024, 1),
                              mk_desc(sd + ((OFF_QA + u * 2048 + ks * 32) >> 4), 16, 1024, 1), (u | ks) != 0);
            wg_commit();
        }
        CK_(4);
    };
    auto colmax = [&]() {
        CK_(5);
        if (tg == 0) { mbar_arrive(BAR(B_FREEQ)); STAMPC(8 + g * 4); }
        const bool b4 = lane & 16, b3 = lane & 8;
        const float m0 = fmaxf(s[0], s[2]), m1 = fmaxf(s[1], s[3]), m2 = fmaxf(s[4], s[6]), m3 = fmaxf(s[5], s[7]);
        const float a0 = fmaxf(b4 ? m2 : m0, __shfl_xor_sync(0xffffffffu, b4 ? m0 : m2, 16));
        const float a1 = fmaxf(b4 ? m3 : m1, __shfl_xor_sync(0xffffffffu, b4 ? m1 : m3, 16));
        float c = fmaxf(b3 ? a1 : a0, __shfl_xor_sync(0xffffffffu, b3 ? a0 : a1, 8));
        c = fmaxf(c, __shfl_xor_sync(0xffffffffu, c, 4));
        if (!(lane & 4)) stsf(wm + (((lane >> 4) * 8 + 2 * q + ((lane >> 3) & 1)) * 4 + w) * 4, c);
        CK_(6);
    };
    auto probs = [&]() {
#pragma unroll
        for (int i = 0; i < 8; i++) pr8[i] = ex2(s[i] - m[(i >> 2) * 2 + (i & 1)]);
        const uint32_t pb = sb + (g ? OFF_P1 : OFF_P0) + w * 512 + lane * 4;
        sts32(pb, pack_bf(pr8[0], pr8[1])); sts32(pb + 256, pack_bf(pr8[2], pr8[3]));
        sts32(pb + 128, pack_bf(pr8[4], pr8[5])); sts32(pb + 256 + 128, pack_bf(pr8[6], pr8[7]));
        if (g == 0 && rr == 0 && w == 0) {
#pragma unroll
            for (int i = 0; i < 4; i++) stsf(st + ST_M0 + ((i >> 1) * 8 + 2 * q + (i & 1)) * 4, m[i]);
        }
        fence_async();
    };
    float la[8];
    auto rowsum = [&](uint32_t pbuf, int acc) {
#pragma unroll
        for (int ks = 0; ks < 4; ks++)
            mma_n16<0, 1>(la, mk_desc(sd + (OFF_ONES >> 4), 128, 256, 0), mk_desc(sd + (pbuf >> 4) + ks * 32, 256, 128, 0), acc | (ks > 0));
    };
    auto pv = [&](uint32_t vbuf, uint32_t pbuf, int acc) {
#pragma unroll
        for (int mt = 0; mt < 4; mt++)
#pragma unroll
            for (int ks = 0; ks < 4; ks++)
                mma_n16<1, 1>(o[mt], mk_desc(sd + ((vbuf + mt * 8192 + ks * 2048) >> 4) + g * 2048, 1024, 1024, 1),
                              mk_desc(sd + (pbuf >> 4) + ks * 32, 256, 128, 0), acc | (ks > 0));
    };
    float f[4];
    auto newmax = [&]() {
#pragma unroll
        for (int i = 0; i < 4; i++) {
            const float4 t4 = ldsf4(st + ST_WMAX + 256 + ((i >> 1) * 8 + 2 * q + (i & 1)) * 16);
            const float mm = fmaxf(fmaxf(fmaxf(t4.x, t4.y), fmaxf(t4.z, t4.w)), m[i]);
            f[i] = m[i] - mm;
            m[i] = mm;
        }
    };
    auto rescale = [&](bool sums) {
#pragma unroll
        for (int i = 0; i < 4; i++) {
            const float fi = ex2(f[i]);
#pragma unroll
            for (int mt = 0; mt < 4; mt++) { o[mt][(i >> 1) * 4 + (i & 1)] *= fi; o[mt][(i >> 1) * 4 + (i & 1) + 2] *= fi; }
            if (sums) { la[(i >> 1) * 4 + (i & 1)] *= fi; la[(i >> 1) * 4 + (i & 1) + 2] *= fi; }
        }
    };
    if (g == 0) {
        scores();
        wg_wait<0>();
        colmax();
        bar_sync(1, 128);
        CKB_(8);
#pragma unroll
        for (int i = 0; i < 4; i++) {
            const float4 t4 = ldsf4(wm + ((i >> 1) * 8 + 2 * q + (i & 1)) * 16);
            m[i] = fmaxf(fmaxf(t4.x, t4.y), fmaxf(t4.z, t4.w));
        }
        probs();
        CK_(9);
        bar_arrive(7, 256);
        bar_sync(1, 128);
        if (tid == 0) STAMPC(9);
        CKB_(11);
        wg_fence();
        pv(OFF_RB, OFF_P0, 0);
        rowsum(OFF_P0, 0);
        wg_commit();
        CK_(12);
        wg_wait<0>();
        CK_(13);
        if (tg == 0) mbar_arrive(BAR(B_FREEB));
        bar_sync(4, 256);
        CKB_(14);
        newmax();
        rescale(true);
        CK_(15);
        bar_sync(3, 256);
        if (tid == 0) STAMPC(13);
        CKB_(17);
        wg_fence();
        rowsum(OFF_P1, 1);
        wg_commit();
        pv(OFF_RA, OFF_P1, 1);
        wg_commit();
        mbar_wait(BAR(B_INIT2), 0);
        wg_wait<1>();
        if (w == 0) {
            const int i = rr & 3;
            const float lv = (i & 2) ? ((i & 1) ? la[5] : la[4]) : ((i & 1) ? la[1] : la[0]);
            const float mv = (i & 2) ? ((i & 1) ? m[3] : m[2]) : ((i & 1) ? m[1] : m[0]);
            st_ll(sc->XS + ((16 * r + (i >> 1) * 8 + 2 * q + (i & 1)) * 64 + pr) * 2 + (rr >> 2), tag, __float_as_uint(mv), __float_as_uint(lv), 0);
        }
        CK_(16);
        wg_wait<0>();
    } else {
      {
        scores();
        bar_sync(7, 256);
        CKB_(11);
        wg_fence();
        pv(OFF_RB, OFF_P0, 0);
        wg_commit();
#pragma unroll
        for (int i = 0; i < 4; i++) m[i] = ldsf(st + ST_M0 + ((i >> 1) * 8 + 2 * q + (i & 1)) * 4);
        wg_wait<1>();
        colmax();
        bar_sync(4, 256);
        CKB_(14);
        newmax();
        probs();
        CK_(15);
        bar_sync(3, 256);
        wg_wait<0>();
        if (tg == 0) mbar_arrive(BAR(B_FREEB));
      }
        rescale(false);
        if (T.mode & 4) bar_sync(6, 256);
        CKB_(17);
        wg_fence();
        pv(OFF_RA, OFF_P1, 1);
        wg_commit();
        mbar_wait(BAR(B_INIT2), 0);
        wg_wait<0>();
    }
    uint4* const pX2 = sc->X2 + ((size_t)((16 * r + 2 * q) * 4 + w) * 64 + pr) * 16 + g * 8 + rr;
    CK_(19);
    if (g == 0 && (T.mode & 4)) bar_arrive(6, 256);
    if (tid == 0) STAMPC(14);
#pragma unroll
    for (int ii = 0; ii < 4; ii++) {
        const int c0 = (ii >> 1) * 4 + (ii & 1);
        st_ll(pX2 + ((ii >> 1) * 8 + (ii & 1)) * (4 * 64 * 16),
              (pack_bf(o[0][c0], o[0][c0 + 2]) & ~1u) | tag, pack_bf(o[1][c0], o[1][c0 + 2]),
              pack_bf(o[2][c0], o[2][c0 + 2]), pack_bf(o[3][c0], o[3][c0 + 2]));
    }
    STAMPW(2);
    CK_(20);
    if (lane == 0) mbar_arrive(BAR(B_EVST));
    if (T.gpos == 1) { phaseG(); phaseH(); }

    {
        const int ci = tg & 15, pg = tg >> 4;
        const uint4* src = sc->X2 + ((size_t)(h * 4 + j) * 64 + 32 * g + pg) * 16 + ci;
        const uint32_t wbuf = st + ST_LSUM + g * 256;
        uint4 sv;
        if (w == 3) {
            if (T.t_2 > 0) wait_until(t0 + T.t_2);
            sv = poll_ll(sc->XS + (h * 64 + 32 * g + lane) * 2, tag, T.bo_2);
            __syncwarp();
            STAMPW(3);
        }
        bar_sync(1 + g, 128);
        CKB_(21);
        spin_clk(T.dl_2);
        uint4 dv[4];
#pragma unroll
        for (int i = 0; i < 4; i++) dv[i] = ld_ll(src + i * 8 * 16);
        if (T.gpos == 3) phaseG();
        if (w == 3) {
            const float mp = __uint_as_float(sv.y), lp = __uint_as_float(sv.z);
            float M = mp;
#pragma unroll
            for (int x = 16; x; x >>= 1) M = fmaxf(M, __shfl_xor_sync(0xffffffffu, M, x));
            const float wp = ex2(mp - M);
            float L = wp * lp;
#pragma unroll
            for (int x = 16; x; x >>= 1) L += __shfl_xor_sync(0xffffffffu, L, x);
            stsf(wbuf + lane * 4, wp * __frcp_rn(L));
        }
        bar_sync(1 + g, 128);
        float wi[4];
#pragma unroll
        for (int i = 0; i < 4; i++) wi[i] = ldsf(wbuf + (i * 8 + pg) * 4);
        CK_(18);
        {
            uint32_t pend = 0;
#pragma unroll
            for (int i = 0; i < 4; i++) if ((dv[i].x ^ tag) & 1u) pend |= 1u << i;
            STAMPW(6);
            int it = 0;
            while (pend && ++it < SPIN_LIMIT) {
                spin_clk(T.bo_2);
#pragma unroll
                for (int i = 0; i < 4; i++) if (pend & (1u << i)) dv[i] = ld_ll(src + i * 8 * 16);
#pragma unroll
                for (int i = 0; i < 4; i++) if (!((dv[i].x ^ tag) & 1u)) pend &= ~(1u << i);
            }
            if (pend) __trap();
        }
        STAMPW(4);
        CK_(22);
        float a8[8];
#pragma unroll
        for (int i = 0; i < 8; i++) a8[i] = 0.f;
#pragma unroll
        for (int i = 0; i < 4; i++) {
            uint4 v = dv[i]; v.x &= ~1u;
            a8[0] += wi[i] * bf_lo(v.x); a8[1] += wi[i] * bf_hi(v.x); a8[2] += wi[i] * bf_lo(v.y); a8[3] += wi[i] * bf_hi(v.y);
            a8[4] += wi[i] * bf_lo(v.z); a8[5] += wi[i] * bf_hi(v.z); a8[6] += wi[i] * bf_lo(v.w); a8[7] += wi[i] * bf_hi(v.w);
        }
        CK_(23);
        const uint32_t red = sb + OFF_RA + g * 4096;
        asm volatile("st.shared.v4.f32 [%0], {%1,%2,%3,%4};" :: "r"(red + tg * 32), "f"(a8[0]), "f"(a8[1]), "f"(a8[2]), "f"(a8[3]) : "memory");
        asm volatile("st.shared.v4.f32 [%0], {%1,%2,%3,%4};" :: "r"(red + tg * 32 + 16), "f"(a8[4]), "f"(a8[5]), "f"(a8[6]), "f"(a8[7]) : "memory");
        bar_sync(1 + g, 128);
        CKB_(24);
        if (tg == 0) mbar_arrive(BAR(B_EVX2));
        const int c2 = tg >> 3, e = tg & 7;
        const uint32_t a = red + c2 * 32 + e * 4;
        const float sum = ((ldsf(a) + ldsf(a + 512)) + (ldsf(a + 1024) + ldsf(a + 1536))) +
                          ((ldsf(a + 2048) + ldsf(a + 2560)) + (ldsf(a + 3072) + ldsf(a + 3584)));
        const int kg = ((c2 >> 3) * 4 + (e >> 1)) * 2 + (e & 1);
        sts16(sb + OFF_Y + OP_CL + kg * 128 + g * 16 + (c2 & 7) * 2, sum);
        fence_async();
    }
    CK_(25);
    bar_sync(3, 256);
    CKB_(26);
    if (tid == 0) STAMPC(16);

    if (T.gpos == 2) phaseG();
    mbar_wait(BAR(B_WUV), 0);
    if (tid == 0) STAMPC(17);
    CK_(27);
    wg_fence();
    gemv_mmajor(acc, sd + (T.o_wuv >> 4) + g * 1024, sd + ((OFF_Y + OP_CL) >> 4), 0, 8, 0);
    wg_commit(); wg_wait<0>();
    CK_(28);
    if (q == 0) {
        const uint32_t o2 = OFF_PA + g * 1024 + r * 512 + ch16;
        st_async4(own_sb + o2, acc, own_sb + OFF_BAR + 8 * B_XD);
        st_async4(peer_sb + o2, acc, peer_sb + OFF_BAR + 8 * B_XD);
    }
    if (tid == 0) STAMPC(18);
    if (T.gpos >= 2) phaseH();
    mbar_wait_cluster(BAR(B_XD), 0);
    CK_(29);
    gather2(sb + OFF_PA, sb + OFF_Y + OP_CX);
    bar_sync(3, 256);
    if (tid == 0) STAMPC(21);
    CKB_(30);

    if (T.gpos == 0) phaseG();
    if (tid == 0) STAMPC(19);
    CK_(31);

    {
        float e0[4], e1[4];
        const uint32_t wot = sd + ((g ? T.o_wo1 : T.o_wo0) >> 4);
        mbar_wait(BAR(B_WO + g), 0);
        if (tid == 0) STAMPC(22);
        CK_(32);
        wg_fence();
        gemv_mmajor(e0, wot,        sd + ((OFF_Y + OP_CX) >> 4), 0, 8, 0);
        gemv_mmajor(e1, wot + 1024, sd + ((OFF_Y + OP_CX) >> 4), 0, 8, 0);
        wg_commit();
        if (glu) {
            if (T.gpos == 0) { phaseH(); bar_sync(3, 256); }
            mbar_wait(BAR(B_WD), 0);
            if (tid == 0) STAMPC(23);
            CK_(33);
            wg_fence();
            gemv_mmajor(e0, sd + (OFF_QA >> 4) + g * 512,       sd + ((OFF_Y + OP_H) >> 4), 0, 2, 1);
            gemv_mmajor(e1, sd + (OFF_QA >> 4) + g * 512 + 256, sd + ((OFF_Y + OP_H) >> 4), 0, 2, 1);
            wg_commit();
        }
        wg_wait<0>();
        CK_(34);
        if (q == 0) {
            uint4* p4 = sc->X4 + pr * 256 + r * 128 + g * 64 + w * 8 + rr;
            st_ll(p4,      (__float_as_uint(e0[0]) & ~1u) | tag, __float_as_uint(e0[1]), __float_as_uint(e0[2]), __float_as_uint(e0[3]));
            st_ll(p4 + 32, (__float_as_uint(e1[0]) & ~1u) | tag, __float_as_uint(e1[1]), __float_as_uint(e1[2]), __float_as_uint(e1[3]));
        }
    }
    STAMPW(5);
    CK_(35);

    if (warp < 2) {
        uint4 v[2];
        if (T.t_4 > 0) wait_until(t0 + T.t_4);
        poll_ll_n<2>(v, sc->X4 + lane * 256 + fcc, 32 * 256, tag, T.bo_4);
        __syncwarp();
        if (tid == 0) STAMPC(31);
        float v0 = __uint_as_float(v[0].x) + __uint_as_float(v[1].x), v1 = __uint_as_float(v[0].y) + __uint_as_float(v[1].y);
        float v2 = __uint_as_float(v[0].z) + __uint_as_float(v[1].z), v3 = __uint_as_float(v[0].w) + __uint_as_float(v[1].w);
        const bool b4 = lane & 16, b3 = lane & 8;
        float k0 = b4 ? v2 : v0, k1 = b4 ? v3 : v1, s0 = b4 ? v0 : v2, s1 = b4 ? v1 : v3;
        k0 += __shfl_xor_sync(0xffffffffu, s0, 16);
        k1 += __shfl_xor_sync(0xffffffffu, s1, 16);
        float k = b3 ? k1 : k0, s = b3 ? k0 : k1;
        k += __shfl_xor_sync(0xffffffffu, s, 8);
        k += __shfl_xor_sync(0xffffffffu, k, 4);
        k += __shfl_xor_sync(0xffffffffu, k, 2);
        k += __shfl_xor_sync(0xffffffffu, k, 1);
        if ((lane & 7) == 0) P.out[fb * 512 + fcol] = __float2bfloat16_rn(k + xres);
        if (tid == 0) STAMP(25);
        CK_(36);
    }
}

typedef CUresult (*PFN_encodeTiled)(CUtensorMap*, CUtensorMapDataType, cuuint32_t, void*, const cuuint64_t*, const cuuint64_t*,
                                    const cuuint32_t*, const cuuint32_t*, CUtensorMapInterleave, CUtensorMapSwizzle,
                                    CUtensorMapL2promotion, CUtensorMapFloatOOBfill);

void make_map(PFN_encodeTiled enc, CUtensorMap* m, const void* ptr, int rank, const cuuint64_t* dims, const cuuint64_t* strides,
              const cuuint32_t* box, CUtensorMapSwizzle sw) {
    cuuint32_t es[3] = {1, 1, 1};
    enc(m, CU_TENSOR_MAP_DATA_TYPE_BFLOAT16, rank, const_cast<void*>(ptr), dims, strides, box, es,
        CU_TENSOR_MAP_INTERLEAVE_NONE, sw, CU_TENSOR_MAP_L2_PROMOTION_NONE, CU_TENSOR_MAP_FLOAT_OOB_FILL_NONE);
}
void make_map2(PFN_encodeTiled enc, CUtensorMap* m, const void* ptr, uint64_t rows, uint64_t cols, uint32_t boxc, uint32_t boxr,
               CUtensorMapSwizzle sw = CU_TENSOR_MAP_SWIZZLE_128B) {
    cuuint64_t dims[2] = {cols, rows}; cuuint64_t strides[1] = {cols * 2}; cuuint32_t box[2] = {boxc, boxr};
    make_map(enc, m, ptr, 2, dims, strides, box, sw);
}

Tune g_tune = { 200, 100, 50, 0, 0, 64, 1500, 150, 0, 0, 4100, 0, 1, 1,
    OFF_R0, OFF_GU, OFF_RB, OFF_R1, -1, B_FREEB, B_FREEB, B_FREE1,
    { {G_WUK,0,0,4,1450,320}, {G_CKV0,0,0,4,2730,320}, {G_CKV1,0,0,4,4010,320}, {G_GU,0,0,4,5290,213}, {G_WO01,0,0,4,6150,160},
      {G_WUV,0,0,4,8400,0}, {G_WO23,0,0,4,-1,0}, {G_WD,0,0,4,-1,0}, {G_END,0,0,0,0,0} },
    { {G_WUV,1,0,4,6800,320}, {G_WO23,1,0,4,8080,160}, {G_WD,1,0,4,8720,106}, {G_END,0,0,0,0,0} } };

}

extern "C" void kernel_launch(void* const* d_in, const int* in_sizes, int n_in, void* d_out, int out_size) {
    (void)in_sizes; (void)n_in; (void)out_size;
    static PFN_encodeTiled enc = nullptr;
    if (!enc) {
        void* fn = nullptr; cudaDriverEntryPointQueryResult qr;
        cudaGetDriverEntryPoint("cuTensorMapEncodeTiled", &fn, cudaEnableDefault, &qr);
        enc = (PFN_encodeTiled)fn;
        cudaFuncSetAttribute(mla_glu_kernel, cudaFuncAttributeMaxDynamicSharedMemorySize, SMEM_BYTES);
    }
    Params P;
    P.x = (const __nv_bfloat16*)d_in[0];
    P.out = (__nv_bfloat16*)d_out;
    static Scratch* scratch = nullptr;
    if (!scratch) cudaGetSymbolAddress((void**)&scratch, g_scratch);
    P.sc = scratch;
    make_map2(enc, &P.wq,  d_in[2], 512, 4096, 64, 128);
    make_map2(enc, &P.wuk, d_in[3], 512, 4096, 64, 32);
    {
        cuuint64_t dims[3] = {4096, 64, 8}; cuuint64_t strides[2] = {8192, 64 * 8192}; cuuint32_t box[3] = {64, 16, 2};
        make_map(enc, &P.wuv, d_in[4], 3, dims, strides, box, CU_TENSOR_MAP_SWIZZLE_128B);
    }
    make_map2(enc, &P.wo,  d_in[5], 4096, 512, 64, 32);
    make_map2(enc, &P.ckv, d_in[1], 8192, 512, 64, 32);
    make_map2(enc, &P.wg,  d_in[7], 512, 1376, 32, 128, CU_TENSOR_MAP_SWIZZLE_64B);
    make_map2(enc, &P.wu,  d_in[8], 512, 1376, 32, 128, CU_TENSOR_MAP_SWIZZLE_64B);
    make_map2(enc, &P.wd,  d_in[9], 1376, 512, 64, 32);
    P.tune = g_tune;
    mla_glu_kernel<<<NCTA, NTHREADS, SMEM_BYTES, cudaStreamPerThread>>>(P);
}
```

```cpp
#include <cuda_runtime.h>
#include <cuda_bf16.h>
#include <cuda.h>
#include <stdint.h>

namespace {

constexpr int NCTA     = 128;
constexpr int NTHREADS = 352;
constexpr int SPIN_LIMIT = 1 << 22;
constexpr int NGLU     = 43;

constexpr uint32_t OFF_RA  = 0;
constexpr uint32_t OFF_RB  = 65536;
constexpr uint32_t OFF_R0  = 131072;
constexpr uint32_t OFF_GU  = OFF_RB + 32768;
constexpr uint32_t OFF_R1  = 163840;
constexpr uint32_t OFF_QA  = 196608;
constexpr uint32_t OFF_XN  = 212992;
constexpr uint32_t OFF_Y   = OFF_XN + 2048;
constexpr uint32_t OP_Q = 0, OP_CL = 32, OP_CX = 64, OP_H = 96;
constexpr uint32_t OFF_P0  = OFF_Y + 2048 + 128;
constexpr uint32_t OFF_P1  = OFF_P0 + 2048;
constexpr uint32_t OFF_PA  = OFF_P1 + 2048;
constexpr uint32_t OFF_PG  = OFF_PA + 2048;
constexpr uint32_t OFF_ST  = OFF_PG + 2048;
constexpr uint32_t ST_WMAX = 0;
constexpr uint32_t ST_LSUM = 512;
constexpr uint32_t ST_M0   = 1024;
constexpr uint32_t ST_M1   = 1088;
constexpr uint32_t ST_STG  = 1280;
constexpr uint32_t OFF_BAR = OFF_ST + 1792;
constexpr uint32_t OFF_T0  = OFF_BAR + 256;
constexpr uint32_t OFF_ONES = OFF_BAR + 512;
constexpr uint32_t OFF_STAMP = OFF_ONES + 2048;
constexpr uint32_t SMEM_USED = OFF_STAMP + 1024;
constexpr uint32_t SMEM_BYTES = SMEM_USED + 1024;
static_assert(SMEM_BYTES <= 232448, "smem");
static_assert((OFF_P0 % 128) == 0 && (OFF_PA % 16) == 0 && (OFF_ST % 16) == 0 && (OFF_BAR % 8) == 0, "align");

enum { B_WQ = 0  , B_WUK = 4, B_CKV = 5  , B_G1 = 9, B_WUV = 10, B_WO = 11  , B_WD = 15,
       B_XA = 16, B_XG = 17, B_XD = 18,
       B_INIT2 = 19, B_EVX2 = 13, B_EVST = 14,
       B_FREEA = 20, B_FREE1 = 21, B_FREEB = 22, B_FREEQ = 23, B_EVX1 = 24, B_T0 = 25, B_EVG = 26, NBARS = 27 };
static_assert(NBARS * 8 <= 256, "bars");

struct Ent { signed char grp, kind, s0, s1; short t, dt; };
enum { G_WUK = 0, G_CKV0, G_CKV1, G_WO01, G_WO23, G_WUV, G_GU, G_WD, G_END };
struct Tune {
    int   bo_1, bo_2, bo_4;
    int   dl_1, dl_2;
    int   mode;
    int   t_init2;
    int   dt_init2;
    int   stag;
    int   t_4;
    int   t_1, t_2;
    int   gpos;
    int   remap;
    int   spare;
    int   o_wo0, o_wo1, o_wuv, o_gu;
    int   f_wo0, f_wo1, f_wuv, f_gu;
    Ent   la[14], lb[14];
};

struct Scratch {
    uint4 X2[128 * 64 * 16];
    uint4 X4[64 * 256];
    uint4 X1[2 * 32 * 64];
    uint4 XS[32 * 64 * 2];
    unsigned epoch[NCTA * 8];
};

struct Params {
    const __nv_bfloat16* x;
    Scratch* sc;
    __nv_bfloat16* out;
    Tune tune;
    alignas(64) CUtensorMap wq, wuk, ckv, wg, wu, wuv, wo, wd;
};

__device__ Scratch g_scratch;
#define CK_(i) do {} while (0)
#define CKB_(i) do {} while (0)
#define STAMP(i) do {} while (0)
#define STAMPC(i) do {} while (0)
#define STAMPW(i) do {} while (0)
__device__ __forceinline__ uint32_t smem_u32(const void* p) { return (uint32_t)__cvta_generic_to_shared(p); }
__device__ __forceinline__ unsigned long long gtime() {
    unsigned long long t; asm volatile("mov.u64 %0, %%globaltimer;" : "=l"(t)); return t;
}
__device__ __forceinline__ void mbar_init(uint32_t bar, uint32_t cnt) {
    asm volatile("mbarrier.init.shared::cta.b64 [%0], %1;" :: "r"(bar), "r"(cnt) : "memory");
}
__device__ __forceinline__ void mbar_expect_tx(uint32_t bar, uint32_t bytes) {
    asm volatile("mbarrier.arrive.expect_tx.shared::cta.b64 _, [%0], %1;" :: "r"(bar), "r"(bytes) : "memory");
}
__device__ __forceinline__ void mbar_arrive(uint32_t bar) {
    asm volatile("mbarrier.arrive.shared::cta.b64 _, [%0];" :: "r"(bar) : "memory");
}
__device__ __forceinline__ void mbar_wait(uint32_t bar, uint32_t parity) {
    uint32_t done; int it = 0;
    do {
        asm volatile("{\n.reg .pred p;\nmbarrier.try_wait.parity.shared::cta.b64 p, [%1], %2;\nselp.u32 %0, 1, 0, p;\n}"
                     : "=r"(done) : "r"(bar), "r"(parity) : "memory");
    } while (!done && ++it < SPIN_LIMIT);
    if (!done) __trap();
}
__device__ __forceinline__ void tma2d(uint32_t dst, const CUtensorMap* m, int c0, int c1, uint32_t bar) {
    asm volatile("cp.async.bulk.tensor.2d.shared::cluster.global.mbarrier::complete_tx::bytes [%0], [%1, {%3,%4}], [%2];"
                 :: "r"(dst), "l"(m), "r"(bar), "r"(c0), "r"(c1) : "memory");
}
__device__ __forceinline__ void tma3d(uint32_t dst, const CUtensorMap* m, int c0, int c1, int c2, uint32_t bar) {
    asm volatile("cp.async.bulk.tensor.3d.shared::cluster.global.mbarrier::complete_tx::bytes [%0], [%1, {%3,%4,%5}], [%2];"
                 :: "r"(dst), "l"(m), "r"(bar), "r"(c0), "r"(c1), "r"(c2) : "memory");
}
__device__ __forceinline__ void tma2d_pf(const CUtensorMap* m, int c0, int c1) {
    asm volatile("cp.async.bulk.prefetch.tensor.2d.L2.global.tile [%0, {%1,%2}];" :: "l"(m), "r"(c0), "r"(c1) : "memory");
}
__device__ __forceinline__ void tma3d_pf(const CUtensorMap* m, int c0, int c1, int c2) {
    asm volatile("cp.async.bulk.prefetch.tensor.3d.L2.global.tile [%0, {%1,%2,%3}];" :: "l"(m), "r"(c0), "r"(c1), "r"(c2) : "memory");
}
__device__ __forceinline__ void pf_map(const CUtensorMap* m) {
    asm volatile("prefetch.tensormap [%0];" :: "l"(m) : "memory");
}
__device__ __forceinline__ void bar_sync(int id, int n) { asm volatile("bar.sync %0, %1;" :: "r"(id), "r"(n) : "memory"); }
__device__ __forceinline__ void bar_arrive(int id, int n) { asm volatile("bar.arrive %0, %1;" :: "r"(id), "r"(n) : "memory"); }
__device__ __forceinline__ bool bar_or(int id, int n, bool flag) {
    uint32_t r;
    asm volatile("{\n.reg .pred p, q;\nsetp.ne.u32 q, %3, 0;\nbarrier.cta.red.or.aligned.pred p, %1, %2, q;\nselp.u32 %0, 1, 0, p;\n}"
                 : "=r"(r) : "r"(id), "r"(n), "r"((uint32_t)flag) : "memory");
    return r != 0;
}
__device__ __forceinline__ void fence_async() { asm volatile("fence.proxy.async.shared::cta;" ::: "memory"); }

__device__ __forceinline__ void st_ll(uint4* p, uint32_t a, uint32_t b, uint32_t c, uint32_t d) {
    asm volatile("st.relaxed.gpu.global.v4.u32 [%0], {%1,%2,%3,%4};" :: "l"(p), "r"(a), "r"(b), "r"(c), "r"(d) : "memory");
}
__device__ __forceinline__ uint4 ld_ll(const uint4* p) {
    uint4 v;
    asm volatile("ld.relaxed.gpu.global.v4.u32 {%0,%1,%2,%3}, [%4];" : "=r"(v.x), "=r"(v.y), "=r"(v.z), "=r"(v.w) : "l"(p) : "memory");
    return v;
}
__device__ __forceinline__ void spin_clk(int n) {
    uint32_t c0, c; asm volatile("mov.u32 %0, %%clock;" : "=r"(c0));
    do { asm volatile("mov.u32 %0, %%clock;" : "=r"(c)); } while ((int)(c - c0) < n);
}
__device__ __forceinline__ uint4 poll_ll(const uint4* p, uint32_t tag, int backoff) {
    uint4 v = ld_ll(p); int it = 0;
    while (((v.x ^ tag) & 1u) && ++it < SPIN_LIMIT) { spin_clk(backoff); v = ld_ll(p); }
    if ((v.x ^ tag) & 1u) __trap();
    v.x &= ~1u;
    return v;
}
template <int N>
__device__ __forceinline__ void poll_ll_n(uint4 (&v)[N], const uint4* p, int stride, uint32_t tag, int backoff) {
    uint32_t pend = 0; int it = 0;
#pragma unroll
    for (int i = 0; i < N; i++) v[i] = ld_ll(p + i * stride);
#pragma unroll
    for (int i = 0; i < N; i++) if ((v[i].x ^ tag) & 1u) pend |= 1u << i;
    while (pend && ++it < SPIN_LIMIT) {
        spin_clk(backoff);
#pragma unroll
        for (int i = 0; i < N; i++) if (pend & (1u << i)) v[i] = ld_ll(p + i * stride);
#pragma unroll
        for (int i = 0; i < N; i++) if (!((v[i].x ^ tag) & 1u)) pend &= ~(1u << i);
    }
    if (pend) __trap();
#pragma unroll
    for (int i = 0; i < N; i++) v[i].x &= ~1u;
}

__device__ __forceinline__ uint64_t mk_desc(uint32_t sa16, uint32_t lbo, uint32_t sbo, uint32_t swz) {
    const uint32_t lo = sa16 + ((lbo >> 4) << 16);
    const uint32_t hi = (sbo >> 4) | (swz << 30);
    return ((uint64_t)hi << 32) | lo;
}
__device__ __forceinline__ void wg_fence()  { asm volatile("wgmma.fence.sync.aligned;" ::: "memory"); }
__device__ __forceinline__ void wg_commit() { asm volatile("wgmma.commit_group.sync.aligned;" ::: "memory"); }
template <int N> __device__ __forceinline__ void wg_wait() { asm volatile("wgmma.wait_group.sync.aligned %0;" :: "n"(N) : "memory"); }

template <int TA, int TB>
__device__ __forceinline__ void mma_n8(float (&d)[4], uint64_t da, uint64_t db, int acc) {
    asm volatile("{\n.reg .pred p;\nsetp.ne.b32 p, %6, 0;\n"
                 "wgmma.mma_async.sync.aligned.m64n8k16.f32.bf16.bf16 {%0,%1,%2,%3}, %4, %5, p, 1, 1, %7, %8;\n}\n"
                 : "+f"(d[0]), "+f"(d[1]), "+f"(d[2]), "+f"(d[3])
                 : "l"(da), "l"(db), "r"(acc), "n"(TA), "n"(TB));
}
template <int TA, int TB>
__device__ __forceinline__ void mma_n16(float (&d)[8], uint64_t da, uint64_t db, int acc) {
    asm volatile("{\n.reg .pred p;\nsetp.ne.b32 p, %10, 0;\n"
                 "wgmma.mma_async.sync.aligned.m64n16k16.f32.bf16.bf16 {%0,%1,%2,%3,%4,%5,%6,%7}, %8, %9, p, 1, 1, %11, %12;\n}\n"
                 : "+f"(d[0]), "+f"(d[1]), "+f"(d[2]), "+f"(d[3]), "+f"(d[4]), "+f"(d[5]), "+f"(d[6]), "+f"(d[7])
                 : "l"(da), "l"(db), "r"(acc), "n"(TA), "n"(TB));
}

__device__ __forceinline__ float bf_round(float v) { return __bfloat162float(__float2bfloat16_rn(v)); }
__device__ __forceinline__ uint32_t pack_bf(float lo, float hi) {
    uint32_t r; asm("cvt.rn.bf16x2.f32 %0, %1, %2;" : "=r"(r) : "f"(hi), "f"(lo)); return r;
}
__device__ __forceinline__ float bf_lo(uint32_t w) { return __uint_as_float(w << 16); }
__device__ __forceinline__ float bf_hi(uint32_t w) { return __uint_as_float(w & 0xFFFF0000u); }
__device__ __forceinline__ float ex2(float v) { float r; asm("ex2.approx.ftz.f32 %0, %1;" : "=f"(r) : "f"(v)); return r; }
__device__ __forceinline__ void sts16(uint32_t a, float v) {
    unsigned short s = __bfloat16_as_ushort(__float2bfloat16_rn(v));
    asm volatile("st.shared.u16 [%0], %1;" :: "r"(a), "h"(s) : "memory");
}
__device__ __forceinline__ void sts32(uint32_t a, uint32_t v) { asm volatile("st.shared.u32 [%0], %1;" :: "r"(a), "r"(v) : "memory"); }
__device__ __forceinline__ void stsf(uint32_t a, float v) { asm volatile("st.shared.f32 [%0], %1;" :: "r"(a), "f"(v) : "memory"); }
__device__ __forceinline__ float ldsf(uint32_t a) { float v; asm volatile("ld.shared.f32 %0, [%1];" : "=f"(v) : "r"(a) : "memory"); return v; }
__device__ __forceinline__ float4 ldsf4(uint32_t a) {
    float4 v; asm volatile("ld.shared.v4.f32 {%0,%1,%2,%3}, [%4];" : "=f"(v.x), "=f"(v.y), "=f"(v.z), "=f"(v.w) : "r"(a) : "memory"); return v;
}
__device__ __forceinline__ void wait_until(unsigned long long t) { while (gtime() < t) {} }

__device__ __forceinline__ uint32_t mapa(uint32_t addr, uint32_t rank) {
    uint32_t r; asm("mapa.shared::cluster.u32 %0, %1, %2;" : "=r"(r) : "r"(addr), "r"(rank)); return r;
}
__device__ __forceinline__ void st_async4(uint32_t dst, const float (&v)[4], uint32_t bar) {
    asm volatile("st.async.weak.shared::cluster.mbarrier::complete_tx::bytes.v4.f32 [%0], {%1,%2,%3,%4}, [%5];"
                 :: "r"(dst), "f"(v[0]), "f"(v[1]), "f"(v[2]), "f"(v[3]), "r"(bar) : "memory");
}
__device__ __forceinline__ void mbar_wait_cluster(uint32_t bar, uint32_t parity) {
    uint32_t done; int it = 0;
    do {
        asm volatile("{\n.reg .pred p;\nmbarrier.try_wait.parity.acquire.cluster.shared::cta.b64 p, [%1], %2;\nselp.u32 %0, 1, 0, p;\n}"
                     : "=r"(done) : "r"(bar), "r"(parity) : "memory");
    } while (!done && ++it < SPIN_LIMIT);
    if (!done) __trap();
}

__device__ __forceinline__ void gemv_mmajor(float (&acc)[4], uint32_t a_base, uint32_t b_base, int ks0, int ks1, int first_acc) {
#pragma unroll
    for (int ks = 0; ks < 8; ks++) {
        if (ks >= ks0 && ks < ks1)
            mma_n8<1, 0>(acc, mk_desc(a_base + ks * 128, 1024, 1024, 1), mk_desc(b_base + ks * 16, 128, 128, 0), (ks > ks0) | first_acc);
    }
}

__global__ void __cluster_dims__(2, 1, 1) __launch_bounds__(NTHREADS, 1)
mla_glu_kernel(const __grid_constant__ Params P)
{
    extern __shared__ uint8_t smem_raw[];
    const int tid = threadIdx.x, lane = tid & 31;
    const int bid = blockIdx.x;
    const unsigned long long t0 = gtime();
    const uint32_t sb = (smem_u32(smem_raw) + 1023u) & ~1023u;
    const uint32_t bars = sb + OFF_BAR;
    auto BAR = [&](int i) { return bars + 8u * i; };
    const int pr = bid >> 1, r = bid & 1;
    int h, j;
    {
        const int i1 = pr - 4, i2 = pr - 36, row = (i2 * 37) >> 8;
        const int hh   = pr < 4 ? 30 + (pr >> 1) : pr < 36 ? ((i1 >> 4) << 3) + (i1 & 7) : 16 + (row >> 1) * 7 + (i2 - row * 7);
        const int half = pr < 4 ? pr & 1 : pr < 36 ? (i1 >> 3) & 1 : row & 1;
        h = hh; j = 2 * half + r;
    }
    if (tid == 288) {
#pragma unroll
        for (int i = 0; i < 4; i++) mbar_init(BAR(B_WQ + i), 1);
        asm volatile("fence.mbarrier_init.release.cluster;" ::: "memory");
#pragma unroll
        for (int i = 0; i < 4; i++) {
            mbar_expect_tx(BAR(B_WQ + i), 16384);
            tma2d(sb + OFF_RA + i * 16384, &P.wq, h * 128 + r * 64, i * 128, BAR(B_WQ + i));
        }
        STAMP(29);
#pragma unroll
        for (int i = 4; i < NBARS; i++) mbar_init(BAR(i), (i == B_EVST || i == B_EVX1) ? 8 : ((i >= B_FREEA && i <= B_FREEQ) || i == B_EVX2 || i == B_EVG) ? 2 : 1);
        mbar_expect_tx(BAR(B_T0), 8); mbar_expect_tx(BAR(B_XA), 2048); mbar_expect_tx(BAR(B_XG), 2048); mbar_expect_tx(BAR(B_XD), 2048);
        asm volatile("fence.mbarrier_init.release.cluster;" ::: "memory");
        fence_async();
    }
    uint4 xa, xb;
    if ((tid & 127) < 32 && tid < 256) {
        const __nv_bfloat16* xr = P.x + (tid >> 7) * 512;
        const uint4* xp = reinterpret_cast<const uint4*>(xr + lane * 16);
        xa = xp[0]; xb = xp[1];
    }
    __syncwarp();
    asm volatile("barrier.cluster.arrive.relaxed.aligned;" ::: "memory");
    const int warp = __shfl_sync(0xffffffffu, tid >> 5, 0);
    const uint32_t sd = (sb & 0x3FFFFu) >> 4;
    const int sl = pr;
    const bool glu = sl < NGLU;
    Scratch* const sc = P.sc;

    if (warp >= 8) {
      if (warp == 9 || warp == 8) {
        bar_arrive(0, NTHREADS);
        asm volatile("barrier.cluster.wait.acquire.aligned;" ::: "memory");
        if (lane == 0) {
            unsigned long long tp;
            if (warp == 8 && r == 0) {
#pragma unroll
                for (int i = 0; i < 2; i++)
                    asm volatile("st.async.weak.shared::cluster.mbarrier::complete_tx::bytes.b64 [%0], %1, [%2];"
                                 :: "r"(mapa(sb + OFF_T0, i)), "l"(t0), "r"(mapa(BAR(B_T0), i)) : "memory");
            }
            mbar_wait_cluster(BAR(B_T0), 0);
            asm volatile("ld.shared.u64 %0, [%1];" : "=l"(tp) : "r"(sb + OFF_T0) : "memory");
            if (P.tune.mode & 64) tp = t0;
            if (warp == 9) { pf_map(&P.wuk); pf_map(&P.ckv); pf_map(&P.wg); pf_map(&P.wu); pf_map(&P.wuv); pf_map(&P.wo); pf_map(&P.wd); }
            const Ent* list = (warp == 9) ? P.tune.la : P.tune.lb;
            const unsigned long long tb = tp + (((pr * 11) & 31) * P.tune.stag >> 5);
#pragma unroll 1
            for (int e = 0; e < 14; e++) {
                const Ent E = list[e];
                if (E.grp >= G_END) break;
                if (E.grp >= G_GU && !glu) continue;
                const bool pf = E.kind != 0;
                unsigned long long tn;
                if (E.t == -2) mbar_wait(BAR(B_EVX2), 0);
                if (E.t == -3) mbar_wait(BAR(B_EVST), 0);
                if (E.t == -4) mbar_wait(BAR(B_EVX1), 0);
                if (E.t == -5) mbar_wait(BAR(B_EVG), 0);
                if (E.t >= 0) tn = tb + E.t; else tn = gtime();
                const int dt = E.dt;
                bool first = true;
                auto step = [&]() { if (first || dt) wait_until(tn); first = false; tn += dt; };
                const int s0 = E.s0, s1 = E.s1;
                switch (E.grp) {
                case G_WUK:
                    if (!pf && s0 == 0) mbar_expect_tx(BAR(B_WUK), 32768);
#pragma unroll 1
                    for (int i = s0; i < s1; i++) {
                        step();
                        if (pf) { tma2d_pf(&P.wuk, h * 128, j * 128 + i * 32); tma2d_pf(&P.wuk, h * 128 + 64, j * 128 + i * 32); }
                        else {
                            tma2d(sb + OFF_R1 + i * 4096,         &P.wuk, h * 128,      j * 128 + i * 32, BAR(B_WUK));
                            tma2d(sb + OFF_R1 + 16384 + i * 4096, &P.wuk, h * 128 + 64, j * 128 + i * 32, BAR(B_WUK));
                        }
                    }
                    break;
                case G_CKV0: case G_CKV1: {
                    const int t = E.grp - G_CKV0;
                    if (!pf && t) mbar_wait(BAR(B_FREEA), 0);
#pragma unroll 1
                    for (int k = s0; k < s1; k++) {
                        const int ps = k >> 1, rh = k & 1;
                        step();
                        if (pf) {
#pragma unroll
                            for (int u = 0; u < 2; u++) tma2d_pf(&P.ckv, (ps * 4 + r * 2 + u) * 64, pr * 128 + t * 64 + rh * 32);
                        } else {
                            if (!rh) mbar_expect_tx(BAR(B_CKV + t * 2 + ps), 32768);
#pragma unroll
                            for (int u = 0; u < 4; u++)
                                tma2d(sb + (t ? OFF_RA : OFF_RB) + (ps * 4 + u) * 8192 + rh * 4096, &P.ckv, (ps * 4 + u) * 64, pr * 128 + t * 64 + rh * 32,
                                      BAR(B_CKV + t * 2 + ps));
                        }
                    }
                    break; }
                case G_WO01: case G_WO23: {
                    const int t = E.grp - G_WO01;
                    const int fo = t ? P.tune.f_wo1 : P.tune.f_wo0;
                    const uint32_t dst = sb + (t ? P.tune.o_wo1 : P.tune.o_wo0);
                    if (!pf) { if (fo >= 0) mbar_wait(BAR(fo), 0); if (s0 == 0) mbar_expect_tx(BAR(B_WO + t), 32768); }
#pragma unroll 1
                    for (int kq = s0; kq < s1; kq++) {
                        step();
                        if (pf) tma2d_pf(&P.wo, r * 256 + t * 128 + (j >> 1) * 64, h * 128 + kq * 32);
                        else {
                            tma2d(dst + kq * 4096,         &P.wo, r * 256 + t * 128,      h * 128 + kq * 32, BAR(B_WO + t));
                            tma2d(dst + 16384 + kq * 4096, &P.wo, r * 256 + t * 128 + 64, h * 128 + kq * 32, BAR(B_WO + t));
                        }
                    }
                    break; }
                case G_WUV:
                    if (!pf) { if (P.tune.f_wuv >= 0) mbar_wait(BAR(P.tune.f_wuv), 0); if (s0 == 0) mbar_expect_tx(BAR(B_WUV), 32768); }
#pragma unroll 1
                    for (int i = s0; i < s1; i++) {
                        step();
                        if (pf) { tma3d_pf(&P.wuv, h * 128, j * 16, i * 2); tma3d_pf(&P.wuv, h * 128 + 64, j * 16, i * 2); }
                        else {
                            tma3d(sb + P.tune.o_wuv + i * 4096,         &P.wuv, h * 128,      j * 16, i * 2, BAR(B_WUV));
                            tma3d(sb + P.tune.o_wuv + 16384 + i * 4096, &P.wuv, h * 128 + 64, j * 16, i * 2, BAR(B_WUV));
                        }
                    }
                    break;
                case G_GU:
                    if (!pf) { if (P.tune.f_gu >= 0) mbar_wait(BAR(P.tune.f_gu), 0); if (s0 == 0) mbar_expect_tx(BAR(B_G1), 32768); }
#pragma unroll 1
                    for (int i = s0; i < s1; i++) {
                        step();
                        if (pf) tma2d_pf((i & 1) ? &P.wu : &P.wg, sl * 32, (2 * r + (i >> 1)) * 128);
                        else tma2d(sb + P.tune.o_gu + i * 8192, (i & 1) ? &P.wu : &P.wg, sl * 32, (2 * r + (i >> 1)) * 128, BAR(B_G1));
                    }
                    break;
                default:
                    if (!pf) { mbar_wait(BAR(B_FREEQ), 0); if (s0 == 0) mbar_expect_tx(BAR(B_WD), 16384); }
#pragma unroll 1
                    for (int i = s0; i < s1; i++) {
                        step();
                        if (pf) tma2d_pf(&P.wd, r * 256 + i * 64, sl * 32);
                        else tma2d(sb + OFF_QA + i * 4096, &P.wd, r * 256 + i * 64, sl * 32, BAR(B_WD));
                    }
                    break;
                }
                STAMP(128 + (warp == 8) * 16 + e);
            }
            STAMP(35 - (warp == 8));
        }
      } else if (warp == 10) {
        const uint32_t ntag = sc->epoch[bid * 8] & 1u;
        if (ntag < 2 && lane == 0) STAMP(26);
        st_ll(sc->X1 + ((lane >> 4) * 32 + h) * 64 + 16 * j + (lane & 15), ntag, 0, 0, 0);
        st_ll(sc->XS + ((16 * r + (lane >> 1)) * 64 + pr) * 2 + (lane & 1), ntag, 0, 0, 0);
#pragma unroll
        for (int i = 0; i < 4; i++) st_ll(sc->X4 + pr * 256 + r * 128 + i * 32 + lane, ntag, 0, 0, 0);
        bar_sync(0, NTHREADS);
        uint4* px2 = sc->X2 + ((size_t)((16 * r) * 4 + (lane >> 4)) * 64 + pr) * 16 + (lane & 15);
        if (!(P.tune.mode & 1)) {
            unsigned long long tn = t0 + P.tune.t_init2;
#pragma unroll 1
            for (int i = 0; i < 32; i++) {
                wait_until(tn); tn += P.tune.dt_init2;
                st_ll(px2 + i * (2 * 64 * 16), ntag, 0, 0, 0);
            }
        }
        __syncwarp();
        asm volatile("fence.acq_rel.cta;" ::: "memory");
        if (lane == 0) { mbar_arrive(BAR(B_INIT2)); STAMP(27); }
      }
      return;
    }

    const int g  = warp >> 2;
    const int w  = warp & 3;
    const int tg = tid & 127;
    const int rr = lane >> 2, q = lane & 3;
    const Tune& T = P.tune;

    if (tid == 0) STAMPC(36);
    const unsigned ep = sc->epoch[bid * 8];
    const int fcc = 2 * bid + (warp & 1);
    const int fcol = 256 * (fcc >> 7) + 64 * ((fcc >> 5) & 3) + 16 * ((fcc >> 3) & 3) + (fcc & 7) + 8 * (lane >> 4);
    const int fb = (lane >> 3) & 1;
    float xres = 0.f;
    if (w == 0) {
        const uint32_t xw[8] = { xa.x, xa.y, xa.z, xa.w, xb.x, xb.y, xb.z, xb.w };
        float xv[16];
#pragma unroll
        for (int i = 0; i < 8; i++) { xv[2 * i] = bf_lo(xw[i]); xv[2 * i + 1] = bf_hi(xw[i]); }
        const float x0 = __shfl_sync(0xffffffffu, xv[0], 0);
        float s = 0.f, s2 = 0.f;
#pragma unroll
        for (int i = 0; i < 16; i++) { const float d = xv[i] - x0; s += d; s2 = fmaf(d, d, s2); }
        if (tid == 0 && s != 12345.f) STAMPC(28);
#pragma unroll
        for (int o = 16; o; o >>= 1) { s += __shfl_xor_sync(0xffffffffu, s, o); s2 += __shfl_xor_sync(0xffffffffu, s2, o); }
        const float md = s * (1.0f / 512.0f);
        const float var = fmaxf(fmaf(-md, md, s2 * (1.0f / 512.0f)), 0.f);
        const float mb = bf_round(x0 + md);
        const float rs = __frcp_rn(bf_round(__fsqrt_rn(bf_round(bf_round(var) + 1e-5f))));
        uint32_t o[8];
#pragma unroll
        for (int i = 0; i < 8; i++) o[i] = pack_bf(bf_round(xv[2 * i] - mb) * rs, bf_round(xv[2 * i + 1] - mb) * rs);
        const uint32_t a = sb + OFF_XN + (lane >> 3) * 32 + (lane & 7) * 256 + g * 16;
        asm volatile("st.shared.v4.u32 [%0], {%1,%2,%3,%4};" :: "r"(a), "r"(o[0]), "r"(o[1]), "r"(o[2]), "r"(o[3]) : "memory");
        asm volatile("st.shared.v4.u32 [%0], {%1,%2,%3,%4};" :: "r"(a + 128), "r"(o[4]), "r"(o[5]), "r"(o[6]), "r"(o[7]) : "memory");
        if (tid == 0) STAMPC(30);
        fence_async();
    }
    if (g == 1) {
        asm volatile("st.shared.v4.u32 [%0], {%1,%1,%1,%1};" :: "r"(sb + OFF_ONES + tg * 16), "r"(0x3F803F80u) : "memory");
        fence_async();
    }
    if (warp < 2) xres = __bfloat162float(P.x[fb * 512 + fcol]);
    const uint32_t tag = (ep + 1u) & 1u;
    const uint32_t ch16 = (w * 8 + rr) * 16;
    const uint32_t own_sb = mapa(sb, r), peer_sb = mapa(sb, r ^ 1);

    bar_sync(0, NTHREADS);
    if (tid == 0) sc->epoch[bid * 8] = ep + 1u;
    if (tid == 0) { STAMPC(0); }
    CK_(0);

    auto gather2 = [&](uint32_t buf, uint32_t op) {
        const int d = tid >> 1, b = tid & 1;
        const uint32_t a = buf + (d >> 6) * 1024 + (((d >> 4) & 3) * 8 + (d & 7)) * 16 + (((d >> 3) & 1) * 2 + b) * 4;
        sts16(op + (d >> 3) * 128 + b * 16 + (d & 7) * 2, ldsf(a) + ldsf(a + 512));
        fence_async();
    };

    float acc[4];
    auto phaseG = [&]() {
        if (glu) {
            float ga[4];
            mbar_wait(BAR(B_G1), 0);
            wg_fence();
#pragma unroll
            for (int ks = 0; ks < 8; ks++)
                mma_n8<1, 0>(ga, mk_desc(sd + ((T.o_gu + ks * 1024) >> 4) + g * 1024, 8192, 512, 2),
                             mk_desc(sd + ((OFF_XN + ks * 256) >> 4) + (2 * r + g) * 2, 128, 128, 0), ks > 0);
            wg_commit(); wg_wait<0>();
            if (q == 0) {
                const uint32_t o2 = OFF_PG + r * 1024 + g * 512 + ch16;
                st_async4(own_sb + o2, ga, own_sb + OFF_BAR + 8 * B_XG);
                st_async4(peer_sb + o2, ga, peer_sb + OFF_BAR + 8 * B_XG);
            }
        }
    };
    auto phaseH = [&]() {
        if (glu && tid < 64) {
            mbar_wait_cluster(BAR(B_XG), 0);
            const int f = tid >> 1, b = tid & 1;
            const uint32_t a = sb + OFF_PG + ((f >> 4) * 8 + (f & 7)) * 16 + (((f >> 3) & 1) * 2 + b) * 4;
            const float gv = bf_round((ldsf(a) + ldsf(a + 512)) + (ldsf(a + 1024) + ldsf(a + 1536)));
            const float uv = bf_round((ldsf(a + 256) + ldsf(a + 768)) + (ldsf(a + 1280) + ldsf(a + 1792)));
            const float sg = bf_round(__fdividef(1.0f, 1.0f + __expf(-gv)));
            sts16(sb + OFF_Y + OP_H + (f >> 3) * 128 + b * 16 + (f & 7) * 2, sg * uv);
            fence_async();
        }
    };
    mbar_wait(BAR(B_WQ + 2 * g), 0);
    wg_fence();
    gemv_mmajor(acc, sd + ((OFF_RA + 2 * g * 16384) >> 4), sd + ((OFF_XN + 2 * g * 32) >> 4), 0, 8, 0);
    wg_commit();
    mbar_wait(BAR(B_WQ + 2 * g + 1), 0);
    if (tid == 0) STAMPC(1);
    wg_fence();
    gemv_mmajor(acc, sd + ((OFF_RA + (2 * g + 1) * 16384) >> 4), sd + ((OFF_XN + (2 * g + 1) * 32) >> 4), 0, 8, 1);
    wg_commit();
    asm volatile("barrier.cluster.wait.acquire.aligned;" ::: "memory");
    wg_wait<0>();
    if (tg == 0) mbar_arrive(BAR(B_FREEA));
    if (q == 0) {
        const uint32_t o = OFF_PA + r * 1024 + g * 512 + ch16;
        st_async4(own_sb + o, acc, own_sb + OFF_BAR + 8 * B_XA);
        st_async4(peer_sb + o, acc, peer_sb + OFF_BAR + 8 * B_XA);
    }
    if (tid == 0) STAMPC(6);
    mbar_wait_cluster(BAR(B_XA), 0);
    if (tid == 0) STAMPC(7);
    gather2(sb + OFF_PA, sb + OFF_Y + OP_Q);
    bar_sync(3, 256);
    if (tid == 0) STAMPC(2);

    mbar_wait(BAR(B_WUK), 0);
    if (tid == 0) STAMPC(3);
    wg_fence();
#pragma unroll
    for (int ks = 0; ks < 8; ks++)
        mma_n8<0, 0>(acc, mk_desc(sd + ((OFF_R1 + (ks >> 2) * 16384 + (ks & 3) * 32) >> 4) + g * 512, 16, 1024, 1),
                     mk_desc(sd + ((OFF_Y + OP_Q + ks * 256) >> 4), 128, 128, 0), ks > 0);
    wg_commit(); wg_wait<0>();
    if (tg == 0) mbar_arrive(BAR(B_FREE1));
    {
        const float qs = 0.08838834764831845f * 1.4426950408889634f;
        const uint32_t stg = sb + OFF_ST + ST_STG + warp * 64;
        if (q == 0) {
            sts16(stg + rr * 2,           acc[0] * qs);
            sts16(stg + 32 + rr * 2,      acc[1] * qs);
            sts16(stg + 16 + rr * 2,      acc[2] * qs);
            sts16(stg + 32 + 16 + rr * 2, acc[3] * qs);
        }
        __syncwarp();
        if (lane < 4) {
            uint4 v;
            asm volatile("ld.shared.v4.u32 {%0,%1,%2,%3}, [%4];" : "=r"(v.x), "=r"(v.y), "=r"(v.z), "=r"(v.w) : "r"(stg + lane * 16) : "memory");
            st_ll(sc->X1 + ((lane >> 1) * 32 + h) * 64 + 16 * j + 8 * g + 2 * w + (lane & 1), (v.x & ~1u) | tag, v.y, v.z, v.w);
        }
    }
    STAMPW(0);
    {
        const uint4* src = sc->X1 + ((pr >> 5) * 32 + 16 * r) * 64;
        uint4 v[4];
        spin_clk(T.dl_1);
        if (T.t_1 > 0) wait_until(t0 + T.t_1);
        poll_ll_n<4>(v, src + tid, 256, tag, T.bo_1);
        __syncwarp();
        if (lane == 0) mbar_arrive(BAR(B_EVX1));
        STAMPW(1);
        CK_(1);
#pragma unroll
        for (int i = 0; i < 4; i++) {
            const int idx = i * 256 + tid, n = idx >> 6, kc = idx & 63;
            const uint32_t a = sb + OFF_QA + (kc >> 3) * 2048 + n * 128 + (((kc & 7) ^ (n & 7)) << 4);
            asm volatile("st.shared.v4.u32 [%0], {%1,%2,%3,%4};" :: "r"(a), "r"(v[i].x), "r"(v[i].y), "r"(v[i].z), "r"(v[i].w) : "memory");
        }
        fence_async();
    }
    bar_sync(3, 256);
    if (tid == 0) STAMPC(5);
    CKB_(2);

    float o[4][8];
    float pr8[8], s[8], m[4];
    const uint32_t st = sb + OFF_ST;
    const uint32_t wm = st + ST_WMAX + g * 256;
    auto scores = [&]() {
        const uint32_t tile = sd + ((g ? OFF_RA : OFF_RB) >> 4);
#pragma unroll
        for (int u = 0; u < 8; u++) {
            if ((u & 3) == 0) mbar_wait(BAR(B_CKV + g * 2 + (u >> 2)), 0);
            wg_fence();
#pragma unroll
            for (int ks = 0; ks < 4; ks++)
                mma_n16<0, 0>(s, mk_desc(tile + ((u * 8192 + ks * 32) >> 4), 16, 1024, 1),
                              mk_desc(sd + ((OFF_QA + u * 2048 + ks * 32) >> 4), 16, 1024, 1), (u | ks) != 0);
            wg_commit();
        }
        CK_(4);
    };
    auto colmax = [&]() {
        CK_(5);
        if (tg == 0) { mbar_arrive(BAR(B_FREEQ)); STAMPC(8 + g * 4); }
        const bool b4 = lane & 16, b3 = lane & 8;
        const float m0 = fmaxf(s[0], s[2]), m1 = fmaxf(s[1], s[3]), m2 = fmaxf(s[4], s[6]), m3 = fmaxf(s[5], s[7]);
        const float a0 = fmaxf(b4 ? m2 : m0, __shfl_xor_sync(0xffffffffu, b4 ? m0 : m2, 16));
        const float a1 = fmaxf(b4 ? m3 : m1, __shfl_xor_sync(0xffffffffu, b4 ? m1 : m3, 16));
        float c = fmaxf(b3 ? a1 : a0, __shfl_xor_sync(0xffffffffu, b3 ? a0 : a1, 8));
        c = fmaxf(c, __shfl_xor_sync(0xffffffffu, c, 4));
        if (!(lane & 4)) stsf(wm + (((lane >> 4) * 8 + 2 * q + ((lane >> 3) & 1)) * 4 + w) * 4, c);
        CK_(6);
    };
    auto probs = [&]() {
#pragma unroll
        for (int i = 0; i < 8; i++) pr8[i] = ex2(s[i] - m[(i >> 2) * 2 + (i & 1)]);
        const uint32_t pb = sb + (g ? OFF_P1 : OFF_P0) + w * 512 + lane * 4;
        sts32(pb, pack_bf(pr8[0], pr8[1])); sts32(pb + 256, pack_bf(pr8[2], pr8[3]));
        sts32(pb + 128, pack_bf(pr8[4], pr8[5])); sts32(pb + 256 + 128, pack_bf(pr8[6], pr8[7]));
        if (g == 0 && rr == 0 && w == 0) {
#pragma unroll
            for (int i = 0; i < 4; i++) stsf(st + ST_M0 + ((i >> 1) * 8 + 2 * q + (i & 1)) * 4, m[i]);
        }
        fence_async();
    };
    float la[8];
    auto rowsum = [&](uint32_t pbuf, int acc) {
#pragma unroll
        for (int ks = 0; ks < 4; ks++)
            mma_n16<0, 1>(la, mk_desc(sd + (OFF_ONES >> 4), 128, 256, 0), mk_desc(sd + (pbuf >> 4) + ks * 32, 256, 128, 0), acc | (ks > 0));
    };
    auto pv = [&](uint32_t vbuf, uint32_t pbuf, int acc) {
#pragma unroll
        for (int mt = 0; mt < 4; mt++)
#pragma unroll
            for (int ks = 0; ks < 4; ks++)
                mma_n16<1, 1>(o[mt], mk_desc(sd + ((vbuf + mt * 8192 + ks * 2048) >> 4) + g * 2048, 1024, 1024, 1),
                              mk_desc(sd + (pbuf >> 4) + ks * 32, 256, 128, 0), acc | (ks > 0));
    };
    float f[4];
    auto newmax = [&]() {
#pragma unroll
        for (int i = 0; i < 4; i++) {
            const float4 t4 = ldsf4(st + ST_WMAX + 256 + ((i >> 1) * 8 + 2 * q + (i & 1)) * 16);
            const float mm = fmaxf(fmaxf(fmaxf(t4.x, t4.y), fmaxf(t4.z, t4.w)), m[i]);
            f[i] = m[i] - mm;
            m[i] = mm;
        }
    };
    auto rescale = [&](bool sums) {
#pragma unroll
        for (int i = 0; i < 4; i++) {
            const float fi = ex2(f[i]);
#pragma unroll
            for (int mt = 0; mt < 4; mt++) { o[mt][(i >> 1) * 4 + (i & 1)] *= fi; o[mt][(i >> 1) * 4 + (i & 1) + 2] *= fi; }
            if (sums) { la[(i >> 1) * 4 + (i & 1)] *= fi; la[(i >> 1) * 4 + (i & 1) + 2] *= fi; }
        }
    };
    if (g == 0) {
        scores();
        wg_wait<0>();
        colmax();
        bar_sync(1, 128);
        CKB_(8);
#pragma unroll
        for (int i = 0; i < 4; i++) {
            const float4 t4 = ldsf4(wm + ((i >> 1) * 8 + 2 * q + (i & 1)) * 16);
            m[i] = fmaxf(fmaxf(t4.x, t4.y), fmaxf(t4.z, t4.w));
        }
        probs();
        CK_(9);
        bar_arrive(7, 256);
        bar_sync(1, 128);
        if (tid == 0) STAMPC(9);
        CKB_(11);
        wg_fence();
        pv(OFF_RB, OFF_P0, 0);
        rowsum(OFF_P0, 0);
        wg_commit();
        CK_(12);
        wg_wait<0>();
        CK_(13);
        if (tg == 0) mbar_arrive(BAR(B_FREEB));
        bar_sync(4, 256);
        CKB_(14);
        newmax();
        rescale(true);
        CK_(15);
        bar_sync(3, 256);
        if (tid == 0) STAMPC(13);
        CKB_(17);
        wg_fence();
        rowsum(OFF_P1, 1);
        wg_commit();
        pv(OFF_RA, OFF_P1, 1);
        wg_commit();
        mbar_wait(BAR(B_INIT2), 0);
        wg_wait<1>();
        if (w == 0) {
            const int i = rr & 3;
            const float lv = (i & 2) ? ((i & 1) ? la[5] : la[4]) : ((i & 1) ? la[1] : la[0]);
            const float mv = (i & 2) ? ((i & 1) ? m[3] : m[2]) : ((i & 1) ? m[1] : m[0]);
            st_ll(sc->XS + ((16 * r + (i >> 1) * 8 + 2 * q + (i & 1)) * 64 + pr) * 2 + (rr >> 2), tag, __float_as_uint(mv), __float_as_uint(lv), 0);
        }
        CK_(16);
        wg_wait<0>();
    } else {
      {
        scores();
        bar_sync(7, 256);
        CKB_(11);
        wg_fence();
        pv(OFF_RB, OFF_P0, 0);
        wg_commit();
#pragma unroll
        for (int i = 0; i < 4; i++) m[i] = ldsf(st + ST_M0 + ((i >> 1) * 8 + 2 * q + (i & 1)) * 4);
        wg_wait<1>();
        colmax();
        bar_sync(4, 256);
        CKB_(14);
        newmax();
        probs();
        CK_(15);
        bar_sync(3, 256);
        wg_wait<0>();
        if (tg == 0) mbar_arrive(BAR(B_FREEB));
      }
        rescale(false);
        if (T.mode & 4) bar_sync(6, 256);
        CKB_(17);
        wg_fence();
        pv(OFF_RA, OFF_P1, 1);
        wg_commit();
        mbar_wait(BAR(B_INIT2), 0);
        wg_wait<0>();
    }
    uint4* const pX2 = sc->X2 + ((size_t)((16 * r + 2 * q) * 4 + w) * 64 + pr) * 16 + g * 8 + rr;
    CK_(19);
    if (g == 0 && (T.mode & 4)) bar_arrive(6, 256);
    if (tid == 0) STAMPC(14);
#pragma unroll
    for (int ii = 0; ii < 4; ii++) {
        const int c0 = (ii >> 1) * 4 + (ii & 1);
        st_ll(pX2 + ((ii >> 1) * 8 + (ii & 1)) * (4 * 64 * 16),
              (pack_bf(o[0][c0], o[0][c0 + 2]) & ~1u) | tag, pack_bf(o[1][c0], o[1][c0 + 2]),
              pack_bf(o[2][c0], o[2][c0 + 2]), pack_bf(o[3][c0], o[3][c0 + 2]));
    }
    STAMPW(2);
    CK_(20);
    if (lane == 0) mbar_arrive(BAR(B_EVST));
    if (T.gpos == 1) { phaseG(); phaseH(); }

    {
        const int ci = tg & 15, pg = tg >> 4;
        const uint4* src = sc->X2 + ((size_t)(h * 4 + j) * 64 + 32 * g + pg) * 16 + ci;
        const uint32_t wbuf = st + ST_LSUM + g * 256;
        uint4 sv;
        if (w == 3) {
            if (T.t_2 > 0) wait_until(t0 + T.t_2);
            sv = poll_ll(sc->XS + (h * 64 + 32 * g + lane) * 2, tag, T.bo_2);
            __syncwarp();
            STAMPW(3);
        }
        bar_sync(1 + g, 128);
        CKB_(21);
        spin_clk(T.dl_2);
        uint4 dv[4];
#pragma unroll
        for (int i = 0; i < 4; i++) dv[i] = ld_ll(src + i * 8 * 16);
        if (tg == 127) mbar_arrive(BAR(B_EVG));
        if (T.gpos == 3) phaseG();
        if (w == 3) {
            const float mp = __uint_as_float(sv.y), lp = __uint_as_float(sv.z);
            float M = mp;
#pragma unroll
            for (int x = 16; x; x >>= 1) M = fmaxf(M, __shfl_xor_sync(0xffffffffu, M, x));
            const float wp = ex2(mp - M);
            float L = wp * lp;
#pragma unroll
            for (int x = 16; x; x >>= 1) L += __shfl_xor_sync(0xffffffffu, L, x);
            stsf(wbuf + lane * 4, wp * __frcp_rn(L));
        }
        bar_sync(1 + g, 128);
        float wi[4];
#pragma unroll
        for (int i = 0; i < 4; i++) wi[i] = ldsf(wbuf + (i * 8 + pg) * 4);
        CK_(18);
        {
            uint32_t pend = 0;
#pragma unroll
            for (int i = 0; i < 4; i++) if ((dv[i].x ^ tag) & 1u) pend |= 1u << i;
            STAMPW(6);
            int it = 0;
            while (pend && ++it < SPIN_LIMIT) {
                spin_clk(T.bo_2);
#pragma unroll
                for (int i = 0; i < 4; i++) if (pend & (1u << i)) dv[i] = ld_ll(src + i * 8 * 16);
#pragma unroll
                for (int i = 0; i < 4; i++) if (!((dv[i].x ^ tag) & 1u)) pend &= ~(1u << i);
            }
            if (pend) __trap();
        }
        STAMPW(4);
        CK_(22);
        float a8[8];
#pragma unroll
        for (int i = 0; i < 8; i++) a8[i] = 0.f;
#pragma unroll
        for (int i = 0; i < 4; i++) {
            uint4 v = dv[i]; v.x &= ~1u;
            a8[0] += wi[i] * bf_lo(v.x); a8[1] += wi[i] * bf_hi(v.x); a8[2] += wi[i] * bf_lo(v.y); a8[3] += wi[i] * bf_hi(v.y);
            a8[4] += wi[i] * bf_lo(v.z); a8[5] += wi[i] * bf_hi(v.z); a8[6] += wi[i] * bf_lo(v.w); a8[7] += wi[i] * bf_hi(v.w);
        }
        CK_(23);
        const uint32_t red = sb + OFF_RA + g * 4096;
        asm volatile("st.shared.v4.f32 [%0], {%1,%2,%3,%4};" :: "r"(red + tg * 32), "f"(a8[0]), "f"(a8[1]), "f"(a8[2]), "f"(a8[3]) : "memory");
        asm volatile("st.shared.v4.f32 [%0], {%1,%2,%3,%4};" :: "r"(red + tg * 32 + 16), "f"(a8[4]), "f"(a8[5]), "f"(a8[6]), "f"(a8[7]) : "memory");
        bar_sync(1 + g, 128);
        CKB_(24);
        if (tg == 0) mbar_arrive(BAR(B_EVX2));
        const int c2 = tg >> 3, e = tg & 7;
        const uint32_t a = red + c2 * 32 + e * 4;
        const float sum = ((ldsf(a) + ldsf(a + 512)) + (ldsf(a + 1024) + ldsf(a + 1536))) +
                          ((ldsf(a + 2048) + ldsf(a + 2560)) + (ldsf(a + 3072) + ldsf(a + 3584)));
        const int kg = ((c2 >> 3) * 4 + (e >> 1)) * 2 + (e & 1);
        sts16(sb + OFF_Y + OP_CL + kg * 128 + g * 16 + (c2 & 7) * 2, sum);
        fence_async();
    }
    CK_(25);
    bar_sync(3, 256);
    CKB_(26);
    if (tid == 0) STAMPC(16);

    if (T.gpos == 2) phaseG();
    mbar_wait(BAR(B_WUV), 0);
    if (tid == 0) STAMPC(17);
    CK_(27);
    wg_fence();
    gemv_mmajor(acc, sd + (T.o_wuv >> 4) + g * 1024, sd + ((OFF_Y + OP_CL) >> 4), 0, 8, 0);
    wg_commit(); wg_wait<0>();
    CK_(28);
    if (q == 0) {
        const uint32_t o2 = OFF_PA + g * 1024 + r * 512 + ch16;
        st_async4(own_sb + o2, acc, own_sb + OFF_BAR + 8 * B_XD);
        st_async4(peer_sb + o2, acc, peer_sb + OFF_BAR + 8 * B_XD);
    }
    if (tid == 0) STAMPC(18);
    if (T.gpos == 2 || T.gpos == 3) phaseH();
    if (T.gpos == 5) phaseG();
    mbar_wait_cluster(BAR(B_XD), 0);
    CK_(29);
    gather2(sb + OFF_PA, sb + OFF_Y + OP_CX);
    bar_sync(3, 256);
    if (tid == 0) STAMPC(21);
    CKB_(30);

    if (T.gpos == 0) phaseG();
    if (tid == 0) STAMPC(19);
    CK_(31);

    {
        float e0[4], e1[4];
        const uint32_t wot = sd + ((g ? T.o_wo1 : T.o_wo0) >> 4);
        mbar_wait(BAR(B_WO + g), 0);
        if (tid == 0) STAMPC(22);
        CK_(32);
        wg_fence();
        gemv_mmajor(e0, wot,        sd + ((OFF_Y + OP_CX) >> 4), 0, 8, 0);
        gemv_mmajor(e1, wot + 1024, sd + ((OFF_Y + OP_CX) >> 4), 0, 8, 0);
        wg_commit();
        if (glu) {
            if (T.gpos == 0 || T.gpos == 5) { phaseH(); bar_sync(3, 256); }
            mbar_wait(BAR(B_WD), 0);
            if (tid == 0) STAMPC(23);
            CK_(33);
            wg_fence();
            gemv_mmajor(e0, sd + (OFF_QA >> 4) + g * 512,       sd + ((OFF_Y + OP_H) >> 4), 0, 2, 1);
            gemv_mmajor(e1, sd + (OFF_QA >> 4) + g * 512 + 256, sd + ((OFF_Y + OP_H) >> 4), 0, 2, 1);
            wg_commit();
        }
        wg_wait<0>();
        CK_(34);
        if (q == 0) {
            uint4* p4 = sc->X4 + pr * 256 + r * 128 + g * 64 + w * 8 + rr;
            st_ll(p4,      (__float_as_uint(e0[0]) & ~1u) | tag, __float_as_uint(e0[1]), __float_as_uint(e0[2]), __float_as_uint(e0[3]));
            st_ll(p4 + 32, (__float_as_uint(e1[0]) & ~1u) | tag, __float_as_uint(e1[1]), __float_as_uint(e1[2]), __float_as_uint(e1[3]));
        }
    }
    STAMPW(5);
    CK_(35);

    if (warp < 2) {
        uint4 v[2];
        if (T.t_4 > 0) wait_until(t0 + T.t_4);
        poll_ll_n<2>(v, sc->X4 + lane * 256 + fcc, 32 * 256, tag, T.bo_4);
        __syncwarp();
        if (tid == 0) STAMPC(31);
        float v0 = __uint_as_float(v[0].x) + __uint_as_float(v[1].x), v1 = __uint_as_float(v[0].y) + __uint_as_float(v[1].y);
        float v2 = __uint_as_float(v[0].z) + __uint_as_float(v[1].z), v3 = __uint_as_float(v[0].w) + __uint_as_float(v[1].w);
        const bool b4 = lane & 16, b3 = lane & 8;
        float k0 = b4 ? v2 : v0, k1 = b4 ? v3 : v1, s0 = b4 ? v0 : v2, s1 = b4 ? v1 : v3;
        k0 += __shfl_xor_sync(0xffffffffu, s0, 16);
        k1 += __shfl_xor_sync(0xffffffffu, s1, 16);
        float k = b3 ? k1 : k0, s = b3 ? k0 : k1;
        k += __shfl_xor_sync(0xffffffffu, s, 8);
        k += __shfl_xor_sync(0xffffffffu, k, 4);
        k += __shfl_xor_sync(0xffffffffu, k, 2);
        k += __shfl_xor_sync(0xffffffffu, k, 1);
        if ((lane & 7) == 0) P.out[fb * 512 + fcol] = __float2bfloat16_rn(k + xres);
        if (tid == 0) STAMP(25);
        CK_(36);
    }
}

typedef CUresult (*PFN_encodeTiled)(CUtensorMap*, CUtensorMapDataType, cuuint32_t, void*, const cuuint64_t*, const cuuint64_t*,
                                    const cuuint32_t*, const cuuint32_t*, CUtensorMapInterleave, CUtensorMapSwizzle,
                                    CUtensorMapL2promotion, CUtensorMapFloatOOBfill);

void make_map(PFN_encodeTiled enc, CUtensorMap* m, const void* ptr, int rank, const cuuint64_t* dims, const cuuint64_t* strides,
              const cuuint32_t* box, CUtensorMapSwizzle sw) {
    cuuint32_t es[3] = {1, 1, 1};
    enc(m, CU_TENSOR_MAP_DATA_TYPE_BFLOAT16, rank, const_cast<void*>(ptr), dims, strides, box, es,
        CU_TENSOR_MAP_INTERLEAVE_NONE, sw, CU_TENSOR_MAP_L2_PROMOTION_NONE, CU_TENSOR_MAP_FLOAT_OOB_FILL_NONE);
}
void make_map2(PFN_encodeTiled enc, CUtensorMap* m, const void* ptr, uint64_t rows, uint64_t cols, uint32_t boxc, uint32_t boxr,
               CUtensorMapSwizzle sw = CU_TENSOR_MAP_SWIZZLE_128B) {
    cuuint64_t dims[2] = {cols, rows}; cuuint64_t strides[1] = {cols * 2}; cuuint32_t box[2] = {boxc, boxr};
    make_map(enc, m, ptr, 2, dims, strides, box, sw);
}

Tune g_tune = { 200, 100, 50, 0, 0, 64, 1500, 150, 0, 0, 4100, 0, 1, 1, 0,
    OFF_R0, OFF_GU, OFF_RB, OFF_R1, -1, B_FREEB, B_FREEB, B_FREE1,
    { {G_WUK,0,0,4,1450,320}, {G_CKV0,0,0,4,2730,320}, {G_CKV1,0,0,4,4010,320}, {G_GU,0,0,4,5290,213}, {G_WO01,0,0,4,6150,160},
      {G_WUV,0,0,4,8400,0}, {G_WO23,0,0,4,-1,0}, {G_WD,0,0,4,-1,0}, {G_END,0,0,0,0,0} },
    { {G_WUV,1,0,4,6800,320}, {G_WO23,1,0,4,8080,160}, {G_WD,1,0,4,8720,106}, {G_END,0,0,0,0,0} } };

}

extern "C" void kernel_launch(void* const* d_in, const int* in_sizes, int n_in, void* d_out, int out_size) {
    (void)in_sizes; (void)n_in; (void)out_size;
    static PFN_encodeTiled enc = nullptr;
    if (!enc) {
        void* fn = nullptr; cudaDriverEntryPointQueryResult qr;
        cudaGetDriverEntryPoint("cuTensorMapEncodeTiled", &fn, cudaEnableDefault, &qr);
        enc = (PFN_encodeTiled)fn;
        cudaFuncSetAttribute(mla_glu_kernel, cudaFuncAttributeMaxDynamicSharedMemorySize, SMEM_BYTES);
    }
    Params P;
    P.x = (const __nv_bfloat16*)d_in[0];
    P.out = (__nv_bfloat16*)d_out;
    static Scratch* scratch = nullptr;
    if (!scratch) cudaGetSymbolAddress((void**)&scratch, g_scratch);
    P.sc = scratch;
    make_map2(enc, &P.wq,  d_in[2], 512, 4096, 64, 128);
    make_map2(enc, &P.wuk, d_in[3], 512, 4096, 64, 32);
    {
        cuuint64_t dims[3] = {4096, 64, 8}; cuuint64_t strides[2] = {8192, 64 * 8192}; cuuint32_t box[3] = {64, 16, 2};
        make_map(enc, &P.wuv, d_in[4], 3, dims, strides, box, CU_TENSOR_MAP_SWIZZLE_128B);
    }
    make_map2(enc, &P.wo,  d_in[5], 4096, 512, 64, 32);
    make_map2(enc, &P.ckv, d_in[1], 8192, 512, 64, 32);
    make_map2(enc, &P.wg,  d_in[7], 512, 1376, 32, 128, CU_TENSOR_MAP_SWIZZLE_64B);
    make_map2(enc, &P.wu,  d_in[8], 512, 1376, 32, 128, CU_TENSOR_MAP_SWIZZLE_64B);
    make_map2(enc, &P.wd,  d_in[9], 1376, 512, 64, 32);
    P.tune = g_tune;
    mla_glu_kernel<<<NCTA, NTHREADS, SMEM_BYTES, cudaStreamPerThread>>>(P);
}
```
